```python
import torch

def _softmax(x, axis=-1):
    return torch.softmax(x, dim=axis)
def _gelu(x):
    return torch.nn.functional.gelu(x, approximate="tanh")
def _silu(x):
    return torch.nn.functional.silu(x)
def _sigmoid(x):
    return torch.sigmoid(x)
def _layernorm(x, axis=-1, eps=1e-5):
    m = x.mean(dim=axis, keepdim=True)
    v = x.var(dim=axis, keepdim=True, unbiased=False)
    return (x - m) / torch.sqrt(v + eps)
def _scatter_add(tgt, idx, src, axis=0):
    return tgt.clone().index_add_(axis, idx, src)
def _segment_sum(src, seg, n):
    out = torch.zeros((n,) + src.shape[1:], dtype=src.dtype)
    return out.index_add_(0, seg, src)
def _pad(x, pw):
    flat = tuple(v for pair in reversed(pw) for v in pair)
    return torch.nn.functional.pad(x, flat)

kernel_name = 'sequential_preLN__ssm_conv_h3__dense_activation_gelu__prompt'

def setup_inputs():

    _w = (lambda a: (lambda t: t.to(torch.bfloat16) if t.is_floating_point() else t)(torch.as_tensor(a)))
    def _A_setup():
        B, S, D = 1, 2048, 576
        ks = 4
        return {
            "q": _w((lambda *s: torch.randn(*s, dtype=torch.bfloat16) * 0.05)(B, S, D)),
            "k": _w((lambda *s: torch.randn(*s, dtype=torch.bfloat16) * 0.2)(B, S, D)),
            "v": _w((lambda *s: torch.randn(*s, dtype=torch.bfloat16) * 0.2)(B, S, D)),
            "shift_k": _w((lambda *s: torch.randn(*s, dtype=torch.bfloat16) * 0.2)(D, ks) * 0.5),
            "ssm_k": _w((lambda *s: torch.randn(*s, dtype=torch.bfloat16) * 0.8)(D, S) * (1.0 / S ** 0.5)),
            "ssm_D": _w((lambda *s: torch.randn(*s, dtype=torch.bfloat16) * 0.2)(D)),
        }
    _A_in = _A_setup()

    def _B_setup():
        B, S, D, F = 1, 2048, 576, 4608
        return {
            "x": _w((lambda *s: torch.randn(*s, dtype=torch.bfloat16) * 0.05)(B, S, D)),
            "w1": _w((lambda *s: torch.randn(*s, dtype=torch.bfloat16) * 0.4)(D, F) * (D ** -0.5)),
            "b1": _w((lambda *s: torch.randn(*s, dtype=torch.bfloat16) * 12.8)(F) * 0.01),
            "w2": _w((lambda *s: torch.randn(*s, dtype=torch.bfloat16) * 0.2)(F, D) * (F ** -0.5)),
            "b2": _w((lambda *s: torch.randn(*s, dtype=torch.bfloat16) * 1.6)(D) * 0.01),
        }
    _B_in = _B_setup()

    return {
        "A_q": _A_in["q"],
        "A_k": _A_in["k"],
        "A_v": _A_in["v"],
        "A_shift_k": _A_in["shift_k"],
        "A_ssm_k": _A_in["ssm_k"],
        "A_ssm_D": _A_in["ssm_D"],
        "B_x": _B_in["x"],
        "B_w1": _B_in["w1"],
        "B_b1": _B_in["b1"],
        "B_w2": _B_in["w2"],
        "B_b2": _B_in["b2"],
    }

def reference(A_q, A_k, A_v, A_shift_k, A_ssm_k, A_ssm_D, B_x, B_w1, B_b1, B_w2, B_b2):
    def _A_ref(q, k, v, shift_k, ssm_k, ssm_D):
        B, S, D = q.shape
        ks = shift_k.shape[-1]
        k_pad = _pad(k, ((0, 0), (ks - 1, 0), (0, 0)))
        k_shift = torch.zeros_like(k)
        for t in range(ks):
            k_shift = k_shift + k_pad[:, t:t + S, :] * shift_k[:, ks - 1 - t][None, None, :]
        kv = k_shift * v
        L = 2 * S
        kv_pad = _pad(kv, ((0, 0), (0, S), (0, 0)))
        kf_pad = _pad(ssm_k, ((0, 0), (0, S)))
        kv_f = (lambda x, axes=(-2,-1): torch.fft.rfft2(x.float(), dim=axes))(kv_pad[:, None, :, :], axes=(1, 2))
        kf_f = (lambda x, axes=(-2,-1): torch.fft.rfft2(x.float(), dim=axes))(kf_pad[:, None, :], axes=(1, 2))
        kf_f = (lambda x, *d: x.permute(*d))(kf_f, 1, 2, 0)
        y_f = kv_f * kf_f[None, :, :, :]
        y = (lambda x, s, axes=(-2,-1): torch.fft.irfft2(x, s=s, dim=axes).to(torch.bfloat16))(y_f, (1, L), axes=(1, 2))[:, 0, :S, :]
        y = y + kv * ssm_D[None, None, :]
        return q * y

    def _B_ref(x, w1, b1, w2, b2):
        h = torch.einsum("bsd,df->bsf", x, w1) + b1
        h = _gelu(h)
        return torch.einsum("bsf,fd->bsd", h, w2) + b2

    x = A_q
    h = x + _A_ref(_layernorm(x, axis=-1), A_k, A_v, A_shift_k, A_ssm_k, A_ssm_D)
    h2 = h + _B_ref(_layernorm(h, axis=-1), B_w1, B_b1, B_w2, B_b2)
    return h2
```

```cpp
#include <cuda_runtime.h>
#include <cuda.h>
#include <cuda_bf16.h>
#include <stdint.h>

namespace {
constexpr int S_ = 2048, D_ = 576, F_ = 4608;

__device__ __forceinline__ uint32_t s2u(const void* p) { return (uint32_t)__cvta_generic_to_shared(p); }
__device__ __forceinline__ uint64_t mkdesc(uint32_t addr, uint32_t lbo, uint32_t sbo, int sw) {
  return (uint64_t)((addr & 0x3FFFF) >> 4) | ((uint64_t)(lbo >> 4) << 16) | ((uint64_t)(sbo >> 4) << 32) | ((uint64_t)sw << 62);
}
__device__ __forceinline__ void mbar_init(uint32_t b, int c) { asm volatile("mbarrier.init.shared::cta.b64 [%0], %1;" ::"r"(b), "r"(c)); }
__device__ __forceinline__ void mbar_expect(uint32_t b, uint32_t tx) { asm volatile("mbarrier.arrive.expect_tx.shared::cta.b64 _, [%0], %1;" ::"r"(b), "r"(tx) : "memory"); }
__device__ __forceinline__ void mbar_arrive(uint32_t b) { asm volatile("mbarrier.arrive.shared::cta.b64 _, [%0];" ::"r"(b) : "memory"); }
__device__ __forceinline__ void mbar_wait(uint32_t b, uint32_t ph) {
  asm volatile("{\n.reg .pred p;\n.reg .u32 n;\nmov.u32 n, 0;\nLW:\nmbarrier.try_wait.parity.shared::cta.b64 p, [%0], %1;\n@p bra LD;\n"
               "add.u32 n, n, 1;\nsetp.lt.u32 p, n, 200000;\n@p bra LW;\nLD:\n}" ::"r"(b), "r"(ph) : "memory");
}
__device__ __forceinline__ void flag_wait(const unsigned* p, unsigned target) {
  asm volatile("{\n.reg .pred p;\n.reg .u32 n, v;\nmov.u32 n, 0;\nLW:\nld.acquire.gpu.global.u32 v, [%0];\nsetp.ge.u32 p, v, %1;\n@p bra LD;\n"
               "add.u32 n, n, 1;\nsetp.lt.u32 p, n, 2000000;\n@p bra LW;\nLD:\n}" ::"l"(p), "r"(target) : "memory");
}
__device__ __forceinline__ void tma2d(uint32_t dst, const CUtensorMap* m, int c0, int c1, uint32_t bar) {
  asm volatile("cp.async.bulk.tensor.2d.shared::cluster.global.mbarrier::complete_tx::bytes [%0], [%1, {%3, %4}], [%2];" ::"r"(dst), "l"(m), "r"(bar), "r"(c0), "r"(c1) : "memory");
}
__device__ __forceinline__ void tma2d_store(const CUtensorMap* m, uint32_t src, int c0, int c1) {
  asm volatile("cp.async.bulk.tensor.2d.global.shared::cta.bulk_group [%0, {%2, %3}], [%1];" ::"l"(m), "r"(src), "r"(c0), "r"(c1) : "memory");
}
__device__ __forceinline__ void bulk_load(uint32_t dst, const void* src, uint32_t bytes, uint32_t bar) {
  asm volatile("cp.async.bulk.shared::cluster.global.mbarrier::complete_tx::bytes [%0], [%1], %2, [%3];" ::"r"(dst), "l"(src), "r"(bytes), "r"(bar) : "memory");
}
__device__ __forceinline__ void bulk_store(void* dst, uint32_t src, uint32_t bytes) {
  asm volatile("cp.async.bulk.global.shared::cta.bulk_group [%0], [%1], %2;" ::"l"(dst), "r"(src), "r"(bytes) : "memory");
}
__device__ __forceinline__ bool elect() { uint32_t p; asm volatile("{.reg .pred p; elect.sync _|p, 0xffffffff; selp.b32 %0,1,0,p;}" : "=r"(p)); return p; }
__device__ __forceinline__ uint32_t pack(float lo, float hi) { uint32_t r; asm("cvt.rn.bf16x2.f32 %0,%1,%2;" : "=r"(r) : "f"(hi), "f"(lo)); return r; }
__device__ __forceinline__ float blo(uint32_t v) { return __uint_as_float(v << 16); }
__device__ __forceinline__ float bhi(uint32_t v) { return __uint_as_float(v & 0xffff0000u); }
__device__ __forceinline__ void lds128(uint32_t& a, uint32_t& b, uint32_t& c, uint32_t& d, uint32_t addr) {
  asm volatile("ld.shared.v4.b32 {%0,%1,%2,%3}, [%4];" : "=r"(a), "=r"(b), "=r"(c), "=r"(d) : "r"(addr) : "memory");
}
__device__ __forceinline__ void sts128(uint32_t addr, uint32_t a, uint32_t b, uint32_t c, uint32_t d) {
  asm volatile("st.shared.v4.b32 [%0], {%1,%2,%3,%4};" ::"r"(addr), "r"(a), "r"(b), "r"(c), "r"(d) : "memory");
}
__device__ __forceinline__ void ldsm4t(uint32_t& a, uint32_t& b, uint32_t& c, uint32_t& d, uint32_t addr) {
  asm volatile("ldmatrix.sync.aligned.m8n8.x4.trans.shared.b16 {%0,%1,%2,%3}, [%4];" : "=r"(a), "=r"(b), "=r"(c), "=r"(d) : "r"(addr) : "memory");
}
__device__ __forceinline__ void stsm4(uint32_t addr, uint32_t a, uint32_t b, uint32_t c, uint32_t d) {
  asm volatile("stmatrix.sync.aligned.m8n8.x4.shared.b16 [%0], {%1,%2,%3,%4};" ::"r"(addr), "r"(a), "r"(b), "r"(c), "r"(d) : "memory");
}
__device__ __forceinline__ void nbar_sync(int id, int n) { asm volatile("bar.sync %0, %1;" ::"r"(id), "r"(n) : "memory"); }
__device__ __forceinline__ void nbar_arrive(int id, int n) { asm volatile("bar.arrive %0, %1;" ::"r"(id), "r"(n) : "memory"); }
#define WG_FENCE() asm volatile("wgmma.fence.sync.aligned;" ::: "memory")
#define WG_COMMIT() asm volatile("wgmma.commit_group.sync.aligned;" ::: "memory")
#define WG_WAIT0() asm volatile("wgmma.wait_group.sync.aligned 0;" ::: "memory")
#define WG_WAIT1() asm volatile("wgmma.wait_group.sync.aligned 1;" ::: "memory")
#define PROXY_FENCE_SMEM() asm volatile("fence.proxy.async.shared::cta;" ::: "memory")
#define PROXY_FENCE_ALL() asm volatile("fence.proxy.async;" ::: "memory")
template <int N> __device__ __forceinline__ void pin(float (&d)[N]) {
#pragma unroll
  for (int i = 0; i < N; i++) asm volatile("" : "+f"(d[i])::"memory");
}
__device__ __forceinline__ void wg64t(float (&d)[32], const uint32_t* a, uint64_t db) {
  asm volatile("wgmma.mma_async.sync.aligned.m64n64k16.f32.bf16.bf16 {%0, %1, %2, %3, %4, %5, %6, %7, %8, %9, %10, %11, %12, %13, %14, %15, %16, %17, %18, %19, %20, %21, %22, %23, %24, %25, %26, %27, %28, %29, %30, %31}, {%32, %33, %34, %35}, %36, 1, 1, 1, 1;"
    : "+f"(d[0]), "+f"(d[1]), "+f"(d[2]), "+f"(d[3]), "+f"(d[4]), "+f"(d[5]), "+f"(d[6]), "+f"(d[7]), "+f"(d[8]), "+f"(d[9]), "+f"(d[10]), "+f"(d[11]), "+f"(d[12]), "+f"(d[13]), "+f"(d[14]), "+f"(d[15]), "+f"(d[16]), "+f"(d[17]), "+f"(d[18]), "+f"(d[19]), "+f"(d[20]), "+f"(d[21]), "+f"(d[22]), "+f"(d[23]), "+f"(d[24]), "+f"(d[25]), "+f"(d[26]), "+f"(d[27]), "+f"(d[28]), "+f"(d[29]), "+f"(d[30]), "+f"(d[31])
    : "r"(a[0]), "r"(a[1]), "r"(a[2]), "r"(a[3]), "l"(db));
}
__device__ __forceinline__ void wg64tz(float (&d)[32], const uint32_t* a, uint64_t db) {
  asm volatile("wgmma.mma_async.sync.aligned.m64n64k16.f32.bf16.bf16 {%0, %1, %2, %3, %4, %5, %6, %7, %8, %9, %10, %11, %12, %13, %14, %15, %16, %17, %18, %19, %20, %21, %22, %23, %24, %25, %26, %27, %28, %29, %30, %31}, {%32, %33, %34, %35}, %36, 0, 1, 1, 1;"
    : "=f"(d[0]), "=f"(d[1]), "=f"(d[2]), "=f"(d[3]), "=f"(d[4]), "=f"(d[5]), "=f"(d[6]), "=f"(d[7]), "=f"(d[8]), "=f"(d[9]), "=f"(d[10]), "=f"(d[11]), "=f"(d[12]), "=f"(d[13]), "=f"(d[14]), "=f"(d[15]), "=f"(d[16]), "=f"(d[17]), "=f"(d[18]), "=f"(d[19]), "=f"(d[20]), "=f"(d[21]), "=f"(d[22]), "=f"(d[23]), "=f"(d[24]), "=f"(d[25]), "=f"(d[26]), "=f"(d[27]), "=f"(d[28]), "=f"(d[29]), "=f"(d[30]), "=f"(d[31])
    : "r"(a[0]), "r"(a[1]), "r"(a[2]), "r"(a[3]), "l"(db));
}
__device__ __forceinline__ void wg64(float (&d)[32], const uint32_t* a, uint64_t db) {
  asm volatile("wgmma.mma_async.sync.aligned.m64n64k16.f32.bf16.bf16 {%0, %1, %2, %3, %4, %5, %6, %7, %8, %9, %10, %11, %12, %13, %14, %15, %16, %17, %18, %19, %20, %21, %22, %23, %24, %25, %26, %27, %28, %29, %30, %31}, {%32, %33, %34, %35}, %36, 1, 1, 1, 0;"
    : "+f"(d[0]), "+f"(d[1]), "+f"(d[2]), "+f"(d[3]), "+f"(d[4]), "+f"(d[5]), "+f"(d[6]), "+f"(d[7]), "+f"(d[8]), "+f"(d[9]), "+f"(d[10]), "+f"(d[11]), "+f"(d[12]), "+f"(d[13]), "+f"(d[14]), "+f"(d[15]), "+f"(d[16]), "+f"(d[17]), "+f"(d[18]), "+f"(d[19]), "+f"(d[20]), "+f"(d[21]), "+f"(d[22]), "+f"(d[23]), "+f"(d[24]), "+f"(d[25]), "+f"(d[26]), "+f"(d[27]), "+f"(d[28]), "+f"(d[29]), "+f"(d[30]), "+f"(d[31])
    : "r"(a[0]), "r"(a[1]), "r"(a[2]), "r"(a[3]), "l"(db));
}
__device__ __forceinline__ void wg64z(float (&d)[32], const uint32_t* a, uint64_t db) {
  asm volatile("wgmma.mma_async.sync.aligned.m64n64k16.f32.bf16.bf16 {%0, %1, %2, %3, %4, %5, %6, %7, %8, %9, %10, %11, %12, %13, %14, %15, %16, %17, %18, %19, %20, %21, %22, %23, %24, %25, %26, %27, %28, %29, %30, %31}, {%32, %33, %34, %35}, %36, 0, 1, 1, 0;"
    : "=f"(d[0]), "=f"(d[1]), "=f"(d[2]), "=f"(d[3]), "=f"(d[4]), "=f"(d[5]), "=f"(d[6]), "=f"(d[7]), "=f"(d[8]), "=f"(d[9]), "=f"(d[10]), "=f"(d[11]), "=f"(d[12]), "=f"(d[13]), "=f"(d[14]), "=f"(d[15]), "=f"(d[16]), "=f"(d[17]), "=f"(d[18]), "=f"(d[19]), "=f"(d[20]), "=f"(d[21]), "=f"(d[22]), "=f"(d[23]), "=f"(d[24]), "=f"(d[25]), "=f"(d[26]), "=f"(d[27]), "=f"(d[28]), "=f"(d[29]), "=f"(d[30]), "=f"(d[31])
    : "r"(a[0]), "r"(a[1]), "r"(a[2]), "r"(a[3]), "l"(db));
}
__device__ __forceinline__ void wg32(float (&d)[16], const uint32_t* a, uint64_t db) {
  asm volatile("wgmma.mma_async.sync.aligned.m64n32k16.f32.bf16.bf16 {%0, %1, %2, %3, %4, %5, %6, %7, %8, %9, %10, %11, %12, %13, %14, %15}, {%16, %17, %18, %19}, %20, 1, 1, 1, 0;"
    : "+f"(d[0]), "+f"(d[1]), "+f"(d[2]), "+f"(d[3]), "+f"(d[4]), "+f"(d[5]), "+f"(d[6]), "+f"(d[7]), "+f"(d[8]), "+f"(d[9]), "+f"(d[10]), "+f"(d[11]), "+f"(d[12]), "+f"(d[13]), "+f"(d[14]), "+f"(d[15])
    : "r"(a[0]), "r"(a[1]), "r"(a[2]), "r"(a[3]), "l"(db));
}
__device__ __forceinline__ void wg32z(float (&d)[16], const uint32_t* a, uint64_t db) {
  asm volatile("wgmma.mma_async.sync.aligned.m64n32k16.f32.bf16.bf16 {%0, %1, %2, %3, %4, %5, %6, %7, %8, %9, %10, %11, %12, %13, %14, %15}, {%16, %17, %18, %19}, %20, 0, 1, 1, 0;"
    : "=f"(d[0]), "=f"(d[1]), "=f"(d[2]), "=f"(d[3]), "=f"(d[4]), "=f"(d[5]), "=f"(d[6]), "=f"(d[7]), "=f"(d[8]), "=f"(d[9]), "=f"(d[10]), "=f"(d[11]), "=f"(d[12]), "=f"(d[13]), "=f"(d[14]), "=f"(d[15])
    : "r"(a[0]), "r"(a[1]), "r"(a[2]), "r"(a[3]), "l"(db));
}
}

__device__ __align__(1024) uint16_t g_kvT[D_ * S_];
__device__ __align__(1024) uint16_t g_xq[D_ * S_ * 2];
__device__ __align__(1024) uint16_t g_hT[D_ * S_];
__device__ __align__(1024) uint4 g_part[16 * 9 * 8 * 2 * 512];
__device__ unsigned g_epoch;
#define TM2(i)
#define TM(i)

namespace {
constexpr uint32_t SB = 1024;
__global__ void __launch_bounds__(288, 1) k_prep(const uint16_t* __restrict__ q, const uint16_t* __restrict__ k, const uint16_t* __restrict__ v,
                                                 const uint16_t* __restrict__ sk) {
  __shared__ float red[2][9][16];
  const int tid = threadIdx.x, lane = tid & 31, wp = tid >> 5, half = lane & 1, b = blockIdx.x;
  const int c0 = wp * 64 + (lane >> 1) * 4, t0 = 16 * b + 8 * half;
  if (tid == 0 && b == 0) g_epoch = g_epoch + 1;
  uint2 kr[11], vr[8], xr[8];
#pragma unroll
  for (int r = 0; r < 11; r++) { int t = t0 - 3 + r; kr[r] = t >= 0 ? __ldg((const uint2*)(k + t * D_ + c0)) : make_uint2(0, 0); }
#pragma unroll
  for (int r = 0; r < 8; r++) vr[r] = __ldg((const uint2*)(v + (t0 + r) * D_ + c0));
  uint4 s0 = __ldg((const uint4*)(sk + c0 * 4)), s1 = __ldg((const uint4*)(sk + c0 * 4 + 8));
#pragma unroll
  for (int r = 0; r < 8; r++) xr[r] = __ldg((const uint2*)(q + (t0 + r) * D_ + c0));
  const uint32_t sw[8] = {s0.x, s0.y, s0.z, s0.w, s1.x, s1.y, s1.z, s1.w};
#pragma unroll
  for (int c = 0; c < 4; c++) {
    const float w0 = blo(sw[2 * c]), w1 = bhi(sw[2 * c]), w2 = blo(sw[2 * c + 1]), w3 = bhi(sw[2 * c + 1]);
    float kf[11], o[8];
#pragma unroll
    for (int r = 0; r < 11; r++) { uint32_t u = (c & 2) ? kr[r].y : kr[r].x; kf[r] = (c & 1) ? bhi(u) : blo(u); }
#pragma unroll
    for (int r = 0; r < 8; r++) {
      uint32_t u = (c & 2) ? vr[r].y : vr[r].x; float vf = (c & 1) ? bhi(u) : blo(u);
      o[r] = fmaf(kf[r + 3], w0, fmaf(kf[r + 2], w1, fmaf(kf[r + 1], w2, kf[r] * w3))) * vf;
    }
    *(uint4*)(g_kvT + (c0 + c) * S_ + t0) = make_uint4(pack(o[0], o[1]), pack(o[2], o[3]), pack(o[4], o[5]), pack(o[6], o[7]));
  }
  float xf[8][4], mu[8], rs[8];
#pragma unroll
  for (int r = 0; r < 8; r++) { xf[r][0] = blo(xr[r].x); xf[r][1] = bhi(xr[r].x); xf[r][2] = blo(xr[r].y); xf[r][3] = bhi(xr[r].y); }
#pragma unroll
  for (int pass = 0; pass < 2; pass++) {
#pragma unroll
    for (int r = 0; r < 8; r++) {
      float s;
      if (pass == 0) s = (xf[r][0] + xf[r][1]) + (xf[r][2] + xf[r][3]);
      else { float a = xf[r][0] - mu[r], bb = xf[r][1] - mu[r], c = xf[r][2] - mu[r], d = xf[r][3] - mu[r]; s = fmaf(a, a, bb * bb) + fmaf(c, c, d * d); }
#pragma unroll
      for (int o = 2; o < 32; o <<= 1) s += __shfl_xor_sync(~0u, s, o);
      if (lane < 2) red[pass][wp][half * 8 + r] = s;
    }
    __syncthreads();
#pragma unroll
    for (int r = 0; r < 8; r++) {
      float s = 0;
#pragma unroll
      for (int w = 0; w < 9; w++) s += red[pass][w][half * 8 + r];
      if (pass == 0) mu[r] = s * (1.f / D_); else rs[r] = rsqrtf(s * (1.f / D_) + 1e-5f);
    }
  }
#pragma unroll
  for (int c = 0; c < 4; c++) {
    uint32_t xp[4], qp[4];
#pragma unroll
    for (int i = 0; i < 4; i++) { xp[i] = pack(xf[2 * i][c], xf[2 * i + 1][c]); qp[i] = pack((xf[2 * i][c] - mu[2 * i]) * rs[2 * i], (xf[2 * i + 1][c] - mu[2 * i + 1]) * rs[2 * i + 1]); }
    uint4* rec = (uint4*)g_xq + ((c0 + c) * 128 + b) * 4 + half;
#pragma unroll
    for (int i = 0; i < 2; i++) {
      const uint32_t kx = half ? xp[2 * i + 1] : xp[2 * i], kq = half ? qp[2 * i + 1] : qp[2 * i];
      const uint32_t ox = __shfl_xor_sync(~0u, half ? xp[2 * i] : xp[2 * i + 1], 1), oq = __shfl_xor_sync(~0u, half ? qp[2 * i] : qp[2 * i + 1], 1);
      rec[2 * i] = half ? make_uint4(ox, kx, oq, kq) : make_uint4(kx, ox, kq, oq);
    }
  }
}

constexpr int CV_P = 8320, CV_PL = 4992, CV_ITEM = CV_P + 2 * CV_PL, CV_YW = 8448, CV_Y = 4 * CV_YW;
constexpr int CV_SMEM = 5 * CV_ITEM + 2 * CV_Y + 256;

template <int C> __device__ __forceinline__ void conv_chain(const uint32_t* a, uint64_t db, float& c0, float& c1, uint32_t ya, uint32_t bfull, uint32_t bempty, uint32_t ph, bool lead) {
  float d[32];
  WG_FENCE();
  wg64z(d, a, db + 64 * C);
#pragma unroll
  for (int m = 1; m < 4 * (C + 1); m++) wg64(d, a + 4 * m, db + (64 * C - 16 * m));
  WG_COMMIT();
  mbar_wait(bempty + 8 * C, ph ^ 1);
  WG_WAIT0(); pin(d);
#pragma unroll
  for (int n = 0; n < 8; n++) {
    float v0 = d[4 * n] + (n ? d[4 * n - 2] : c0), v1 = d[4 * n + 1] + (n ? d[4 * n - 1] : c1);
    asm volatile("st.shared.v2.f32 [%0], {%1,%2};" ::"r"(ya + (32 * C + 4 * n) * 64), "f"(v0), "f"(v1) : "memory");
  }
  asm volatile("add.f32 %0, %1, 0f80000000;" : "=f"(c0) : "f"(d[30])); asm volatile("add.f32 %0, %1, 0f80000000;" : "=f"(c1) : "f"(d[31]));
  __syncwarp();
  if (lead) mbar_arrive(bfull + 8 * C);
}
__device__ __forceinline__ void conv_item(const uint32_t* a, uint32_t planes, uint32_t ya, uint32_t bfull, uint32_t bempty, uint32_t ph, bool lead) {
  const uint64_t db = mkdesc(planes + 768, CV_PL, 128, 0);
  float c0 = 0.f, c1 = 0.f;
  conv_chain<0>(a, db, c0, c1, ya, bfull, bempty, ph, lead); conv_chain<1>(a, db, c0, c1, ya, bfull, bempty, ph, lead);
  conv_chain<2>(a, db, c0, c1, ya, bfull, bempty, ph, lead); conv_chain<3>(a, db, c0, c1, ya, bfull, bempty, ph, lead);
}
__device__ __forceinline__ void conv_lda(uint32_t* a, uint32_t pa) {
#pragma unroll
  for (int m = 0; m < 16; m++)
#pragma unroll
    for (int r = 0; r < 4; r++) asm volatile("ld.shared.b32 %0, [%1];" : "=r"(a[4 * m + r]) : "r"(pa + (128 * m + 64 * (r & 1) - 8 * (r >> 1)) * 4) : "memory");
}

__global__ void __launch_bounds__(384, 1) k_conv(const uint16_t* __restrict__ ssk, const uint16_t* __restrict__ Dv) {
  extern __shared__ __align__(1024) uint8_t smem_raw[];
  constexpr uint32_t sb = SB;
  if (s2u(smem_raw) != SB) return;
  const int tid = threadIdx.x, wg = __shfl_sync(~0u, tid >> 7, 0), tl = tid & 127, w = tl >> 5, lane = tid & 31, g = lane >> 2, t4 = lane & 3, b = blockIdx.x;
  const int nit = b < 64 ? 5 : 4;
  const uint32_t ybase = sb + 5 * CV_ITEM, bar = ybase + 2 * CV_Y;
  if (tid == 0) { for (int i = 0; i < 5; i++) mbar_init(bar + 8 * i, 1); for (int i = 0; i < 16; i++) mbar_init(bar + 40 + 8 * i, 4); asm volatile("fence.mbarrier_init.release.cluster;" ::: "memory"); }
  for (int i = tid; i < 5 * 2 * 49; i += 384) { int it = i / 98, r = i % 98, pl = r / 49, row = r % 49;
    if (pl == 0 || row < 48) sts128(sb + it * CV_ITEM + CV_P + pl * CV_PL + row * 16, 0, 0, 0, 0); }
  if (tid < 96) { int y = tid / 12, r = tid % 12; sts128(ybase + y * CV_YW + r * 16, 0, 0, 0, 0); }
  __syncthreads();
  if (tid == 0) {
    for (int it = 0; it < nit; it++) { int ch = b + 128 * it; uint32_t base = sb + it * CV_ITEM + CV_P;
      mbar_expect(bar + 8 * it, 8192);
      bulk_load(base + 768 + 16, g_kvT + ch * S_, 4096, bar + 8 * it);
      bulk_load(base + CV_PL + 768, g_kvT + ch * S_, 4096, bar + 8 * it); }
  }
  if (tid < 256) for (int it = 0; it < nit; it++) {
    int ch = b + 128 * it; const uint16_t* kp = ssk + ch * S_ + tid * 8;
    uint4 u = __ldg((const uint4*)kp); uint32_t pv = tid ? __ldg((const uint32_t*)(kp - 2)) : 0u;
    if (tid == 0) { float k0 = blo(u.x) + __uint_as_float((uint32_t)Dv[ch] << 16); u.x = (u.x & 0xffff0000u) | (pack(k0, 0.f) & 0xffffu);
      sts128(sb + it * CV_ITEM, 0, 0, 0, 0); sts128(sb + it * CV_ITEM + 16, 0, 0, 0, 0); }
    uint32_t pa = sb + it * CV_ITEM + 32 + tid * 32;
    sts128(pa, __byte_perm(u.x, pv, 0x7610), __byte_perm(u.x, u.x, 0x1032), __byte_perm(u.y, u.x, 0x7610), __byte_perm(u.y, u.y, 0x1032));
    sts128(pa + 16, __byte_perm(u.z, u.y, 0x7610), __byte_perm(u.z, u.z, 0x1032), __byte_perm(u.w, u.z, 0x7610), __byte_perm(u.w, u.w, 0x1032));
  }
  PROXY_FENCE_SMEM();
  __syncthreads();
  if (wg == 2) {
    asm volatile("setmaxnreg.dec.sync.aligned.u32 40;");
    const uint32_t yr = ybase + (tl >> 2) * 64 + (((tl & 3) ^ ((tl >> 2) & 2)) * 16);
    const int nu = nit * 4;
    auto item_of = [&](int u) { return u < 16 ? (u >> 3) * 2 + (u & 1) : 4; };
    auto chain_of = [&](int u) { return u < 16 ? (u >> 1) & 3 : u - 16; };
    uint4 nx = __ldcg((const uint4*)g_xq + b * 512 + tl);
#pragma unroll 1
    for (int u = 0; u < nu; u++) {
      const int it = item_of(u), c = chain_of(u), g2 = it & 1, ch = b + 128 * it;
      const uint4 xq = nx;
      if (u + 1 < nu) nx = __ldcg((const uint4*)g_xq + (b + 128 * item_of(u + 1)) * 512 + chain_of(u + 1) * 128 + tl);
      mbar_wait(bar + 40 + 8 * (g2 * 4 + c), (it >> 1) & 1);
      float s0, s1, s2, s3;
      const uint32_t ya = yr + g2 * CV_Y + c * 2048;
      uint32_t u0[4], u1[4], u2[4], u3[4];
#pragma unroll
      for (int ww = 0; ww < 4; ww++) lds128(u0[ww], u1[ww], u2[ww], u3[ww], ya + ww * CV_YW);
      s0 = (__uint_as_float(u0[0]) + __uint_as_float(u0[1])) + (__uint_as_float(u0[2]) + __uint_as_float(u0[3]));
      s1 = (__uint_as_float(u1[0]) + __uint_as_float(u1[1])) + (__uint_as_float(u1[2]) + __uint_as_float(u1[3]));
      s2 = (__uint_as_float(u2[0]) + __uint_as_float(u2[1])) + (__uint_as_float(u2[2]) + __uint_as_float(u2[3]));
      s3 = (__uint_as_float(u3[0]) + __uint_as_float(u3[1])) + (__uint_as_float(u3[2]) + __uint_as_float(u3[3]));
      __syncwarp();
      if (lane == 0) { if (c > 0) mbar_arrive(bar + 40 + 64 + 8 * (g2 * 4 + c - 1)); if (c == 3) mbar_arrive(bar + 40 + 64 + 8 * (g2 * 4 + 3)); }
      uint2 o;
      o.x = pack(fmaf(blo(xq.z), s0, blo(xq.x)), fmaf(bhi(xq.z), s2, bhi(xq.x)));
      o.y = pack(fmaf(blo(xq.w), s1, blo(xq.y)), fmaf(bhi(xq.w), s3, bhi(xq.y)));
      *(uint2*)(g_hT + ch * S_ + c * 512 + tl * 4) = o;
      if (c == 3) TM(24 + it);
    }
  } else {
    asm volatile("setmaxnreg.inc.sync.aligned.u32 232;");
    const int P0 = t4 + w;
    const uint32_t ya = ybase + wg * CV_Y + w * CV_YW + P0 * 64 + (((g >> 1) ^ (P0 & 2)) * 16) + (g & 1) * 8;
    const uint32_t bfull = bar + 40 + wg * 32, bempty = bfull + 64;
    const uint32_t ib = sb + wg * CV_ITEM, pa = ib + (8 + 16 * w + g + 8 - 2 * t4) * 4;
    uint32_t a0[64], a1[64];
    TM(0 + wg * 8);
    conv_lda(a0, pa); conv_lda(a1, pa + 2 * CV_ITEM);
    mbar_wait(bar + 8 * wg, 0);
    TM(1 + wg * 8);
    conv_item(a0, ib + CV_P, ya, bfull, bempty, 0, lane == 0);
    TM(2 + wg * 8);
    const bool five = wg == 0 && nit == 5;
    if (five) conv_lda(a0, pa + 4 * CV_ITEM);
    mbar_wait(bar + 8 * (wg + 2), 0);
    conv_item(a1, ib + 2 * CV_ITEM + CV_P, ya, bfull, bempty, 1, lane == 0);
    TM(3 + wg * 8);
    if (five) { mbar_wait(bar + 8 * 4, 0); conv_item(a0, ib + 4 * CV_ITEM + CV_P, ya, bfull, bempty, 0, lane == 0); }
    TM(4 + wg * 8);
  }
}

template <int V> struct IC { static constexpr int value = V; };
constexpr int ST_B = 144 * 128;
constexpr int M_RING = 0, M_PARK = 4 * ST_B;
constexpr int M_BIAS = M_PARK + 18 * 8192, M_B2 = M_BIAS + 576 * 4, M_BAR = M_B2 + 64 * 4;
constexpr int B_FULL = 0, B_EMPTY = 4, B_A = 8, B_STEP = 10, B_H = 12, B_SLAB = 13, B_NB = 14;
constexpr int M_SMEM = M_BAR + B_NB * 8;

__device__ __forceinline__ float gelu2(float x) {
  float u = x * fmaf(x * x, 0.035677408136f, 0.7978845608f), t;
  asm("tanh.approx.f32 %0,%1;" : "=f"(t) : "f"(u));
  return fmaf(x, t, x);
}
__device__ __forceinline__ void gelu_slice(const float* e, float r0, float r1, uint32_t ba, uint32_t& p0, uint32_t& p1, uint32_t& p2, uint32_t& p3) {
  float b0, b1, b2, b3;
  asm volatile("ld.shared.v2.f32 {%0,%1}, [%2];" : "=f"(b0), "=f"(b1) : "r"(ba) : "memory");
  asm volatile("ld.shared.v2.f32 {%0,%1}, [%2];" : "=f"(b2), "=f"(b3) : "r"(ba + 32) : "memory");
  p0 = pack(gelu2(fmaf(e[0], r0, b0)), gelu2(fmaf(e[1], r0, b1))); p1 = pack(gelu2(fmaf(e[2], r1, b0)), gelu2(fmaf(e[3], r1, b1)));
  p2 = pack(gelu2(fmaf(e[4], r0, b2)), gelu2(fmaf(e[5], r0, b3))); p3 = pack(gelu2(fmaf(e[6], r1, b2)), gelu2(fmaf(e[7], r1, b3)));
}
__device__ __forceinline__ void mma_stage(float (&d)[32], const uint32_t (&a)[144], int sg) {
  const uint64_t db = mkdesc(SB + M_RING + sg * ST_B, 16384, 1024, 1);
  WG_FENCE();
#pragma unroll
  for (int u = 0; u < 9; u++) { if ((sg | u) == 0) wg64tz(d, &a[0], db); else wg64t(d, &a[(sg * 9 + u) * 4], db + u * 128); }
  WG_COMMIT();
}
template <bool EPI> __device__ __forceinline__ void chunk1(float (&d)[32], float (&e)[32], const uint32_t (&a)[144], uint32_t bars, uint32_t ph, uint32_t park, uint32_t ba, bool leader, float r0, float r1) {
#pragma unroll
  for (int sg = 0; sg < 4; sg++) {
    mma_stage(d, a, sg);
    mbar_wait(bars + 8 * (B_FULL + ((sg + 1) & 3)), sg == 3 ? ph ^ 1 : ph);
    if (EPI) { uint32_t p0, p1, p2, p3; gelu_slice(&e[8 * sg], r0, r1, ba + sg * 64, p0, p1, p2, p3); sts128(park + sg * 2048, p0, p1, p2, p3); }
    WG_WAIT0();
    if (leader) mbar_arrive(bars + 8 * (B_EMPTY + sg));
  }
  pin(d);
}
__device__ __forceinline__ void ld_part(uint32_t (&u)[16], const uint4* p) {
#pragma unroll
  for (int i = 0; i < 4; i++) asm volatile("ld.relaxed.gpu.global.v4.u32 {%0,%1,%2,%3}, [%4];" : "=r"(u[4 * i]), "=r"(u[4 * i + 1]), "=r"(u[4 * i + 2]), "=r"(u[4 * i + 3]) : "l"(p + i * 128) : "memory");
}
__device__ __forceinline__ void poll_part(uint32_t (&u)[16], const uint4* p, uint32_t tag) {
  asm volatile("{\n.reg .pred p;\n.reg .u32 n, t, r;\nmov.u32 n, 0;\nLW:\nlop3.b32 t, %0, %4, %17, 0x7e;\nlop3.b32 r, %8, %12, %17, 0x7e;\nor.b32 t, t, r;\nand.b32 t, t, 1;\nsetp.eq.u32 p, t, 0;\n@p bra LD;\n"
               "ld.relaxed.gpu.global.v4.u32 {%0,%1,%2,%3}, [%16];\nld.relaxed.gpu.global.v4.u32 {%4,%5,%6,%7}, [%16+2048];\n"
               "ld.relaxed.gpu.global.v4.u32 {%8,%9,%10,%11}, [%16+4096];\nld.relaxed.gpu.global.v4.u32 {%12,%13,%14,%15}, [%16+6144];\n"
               "add.u32 n, n, 1;\nsetp.lt.u32 p, n, 1000000;\n@p bra LW;\nLD:\n}"
               : "+r"(u[0]), "+r"(u[1]), "+r"(u[2]), "+r"(u[3]), "+r"(u[4]), "+r"(u[5]), "+r"(u[6]), "+r"(u[7]), "+r"(u[8]), "+r"(u[9]), "+r"(u[10]), "+r"(u[11]),
                 "+r"(u[12]), "+r"(u[13]), "+r"(u[14]), "+r"(u[15]) : "l"(p), "r"(tag) : "memory");
  __syncwarp();
}
template <int I0, int I1> __device__ __forceinline__ void add_part(float (&s)[32], const uint32_t (&u)[16]) {
#pragma unroll
  for (int i = I0; i < I1; i++) { s[2 * i] += blo(u[i]); s[2 * i + 1] += bhi(u[i]); }
#pragma unroll
  for (int i = 2 * I0; i < 2 * I1; i++) asm volatile("" : "+f"(s[i])::"memory");
}

__global__ void __launch_bounds__(384, 1) k_mlp(const __grid_constant__ CUtensorMap tm_h, const __grid_constant__ CUtensorMap tm_w1,
                                                const __grid_constant__ CUtensorMap tm_w2, const __grid_constant__ CUtensorMap tm_o,
                                                const uint16_t* __restrict__ b1, const uint16_t* __restrict__ b2, const uint16_t* __restrict__ w2, uint16_t* __restrict__ out) {
  extern __shared__ __align__(1024) uint8_t smem_raw[];
  constexpr uint32_t sb = SB, bars = sb + M_BAR;
  if (s2u(smem_raw) != SB) return;
  const int tid = threadIdx.x, wg = __shfl_sync(~0u, tid >> 7, 0), lane = tid & 31;
  const int m = blockIdx.x >> 3, j = blockIdx.x & 7;
  if (tid == 0) {
    for (int i = 0; i < 4; i++) { mbar_init(bars + 8 * (B_FULL + i), 1); mbar_init(bars + 8 * (B_EMPTY + i), 2); }
    for (int i = 0; i < 2; i++) { mbar_init(bars + 8 * (B_A + i), 1); mbar_init(bars + 8 * (B_STEP + i), 8); mbar_init(bars + 8 * (B_H + i), 1); }
    asm volatile("fence.mbarrier_init.release.cluster;" ::: "memory");
  }
  for (int i = tid; i < 640; i += 384) { float bv = i < 576 ? blo(b1[j * 576 + i]) : 2.f * blo(b2[j * 64 + i - 576]); asm volatile("st.shared.f32 [%0], %1;" ::"r"(sb + M_BIAS + i * 4), "f"(bv) : "memory"); }
  const uint32_t tag = __ldcg(&g_epoch) & 1u;
  __syncthreads();
  if (wg == 2) {
    asm volatile("setmaxnreg.dec.sync.aligned.u32 24;");
    const int pw = __shfl_sync(~0u, (tid >> 5) & 3, 0);
    if (pw == 0) {
      if (elect()) {
        for (int g2 = 0; g2 < 2; g2++) { mbar_expect(bars + 8 * (B_A + g2), 9 * 8192);
          for (int s = 0; s < 9; s++) tma2d(sb + M_PARK + (g2 * 9 + s) * 8192, &tm_h, m * 128 + g2 * 64, s * 64, bars + 8 * (B_A + g2)); }
      }
      __syncwarp();
      for (int c = 0; c < 18; c++) {
        const bool p2 = c >= 9; const int s = c - 9;
        const int col = p2 ? (s == 0 ? 8 : (j ^ (8 - s))) * 64 : j * 576 + c * 64, row = p2 ? j * 576 : 0;
        for (int sg = 0; sg < 4; sg++) {
          mbar_wait(bars + 8 * (B_EMPTY + sg), (c & 1) ^ 1);
          if (elect()) { mbar_expect(bars + 8 * (B_FULL + sg), ST_B); tma2d(sb + M_RING + sg * ST_B, p2 ? &tm_w2 : &tm_w1, col, row + sg * 144, bars + 8 * (B_FULL + sg)); }
          __syncwarp();
        }
      }
    } else if (pw == 1) {
      if (elect()) asm volatile("cp.async.bulk.prefetch.L2.global [%0], %1;" ::"l"(w2 + (j * 576 + m * 36) * D_), "r"(36 * D_ * 2) : "memory");
      const int g = lane >> 2, t4 = lane & 3;
      mbar_wait(bars + 8 * B_STEP, 0);
      if (elect()) {
        PROXY_FENCE_SMEM();
        mbar_expect(bars + 8 * B_H, 3 * 8192);
        for (int g2 = 0; g2 < 2; g2++) tma2d(sb + M_PARK + (g2 * 9 + 7) * 8192, &tm_h, m * 128 + g2 * 64, j * 64, bars + 8 * B_H);
        tma2d(sb + M_PARK + 6 * 8192, &tm_h, m * 128 + (j >> 2) * 64, 512, bars + 8 * B_H);
      }
      __syncwarp();
      mbar_wait(bars + 8 * (B_STEP + 1), 0);
      const uint32_t pa = sb + M_PARK + lane * 16;
#pragma unroll 1
      for (int it = 0; it < 100000; it++) {
        if (elect()) { PROXY_FENCE_SMEM(); mbar_expect(bars + 8 * B_SLAB, 16384); bulk_load(sb + M_PARK, g_part + ((m * 9 + 8) * 8 + j) * 1024, 16384, bars + 8 * B_SLAB); }
        __syncwarp();
        mbar_wait(bars + 8 * B_SLAB, it & 1);
        uint32_t bad = 0;
#pragma unroll 8
        for (int i = 0; i < 32; i++) { uint32_t u; asm volatile("ld.shared.b32 %0, [%1];" : "=r"(u) : "r"(pa + i * 512) : "memory"); bad |= u ^ tag; }
        if (!__any_sync(~0u, bad & 1)) break;
      }
      uint16_t* op = out + (m * 128 + j * 16 + 8 * ((g >> 1) & 1) + 2 * (g >> 2) + (g & 1)) * D_ + 512 + 2 * t4;
      const uint32_t hl = sb + M_PARK + 6 * 8192 + (lane & 7) * 128 + (((((lane >> 3) & 1) + 2 * (j & 3)) ^ (lane & 7)) * 16);
      mbar_wait(bars + 8 * B_H, 0);
#pragma unroll 1
      for (int i = 0; i < 8; i++) {
        const uint32_t bb = __ldg((const uint32_t*)(b2 + 512 + i * 8 + 2 * t4));
        uint32_t h0, h1;
        asm volatile("ldmatrix.sync.aligned.m8n8.x2.trans.shared.b16 {%0,%1}, [%2];" : "=r"(h0), "=r"(h1) : "r"(hl + i * 1024) : "memory");
        float s0 = 0, s1 = 0, s2 = 0, s3 = 0;
#pragma unroll
        for (int src = 0; src < 8; src++) {
          uint32_t ux, uy;
          asm volatile("ld.shared.v2.b32 {%0,%1}, [%2];" : "=r"(ux), "=r"(uy) : "r"(pa + (i >> 1) * 512 + (i & 1) * 8 + src * 2048) : "memory");
          s0 += blo(ux); s1 += bhi(ux); s2 += blo(uy); s3 += bhi(uy);
        }
        *(uint32_t*)(op + i * 8) = pack(blo(h0) + fmaf(0.5f, s0, blo(bb)), bhi(h0) + fmaf(0.5f, s1, bhi(bb)));
        *(uint32_t*)(op + i * 8 + 4 * D_) = pack(blo(h1) + fmaf(0.5f, s2, blo(bb)), bhi(h1) + fmaf(0.5f, s3, bhi(bb)));
      }
    }
  } else {
    asm volatile("setmaxnreg.inc.sync.aligned.u32 240;");
    const int tl = tid & 127, w = tl >> 5, t4 = lane & 3;
    const bool leader = tl == 0;
    const uint32_t reg = sb + M_PARK + wg * 9 * 8192;
    const uint32_t lma = (((lane >> 4) * 8 + (lane & 7)) * 128) + (((((lane >> 3) & 1) + 2 * w) ^ (lane & 7)) * 16);
    uint32_t a[144];
    TM(32 + wg * 16);
    mbar_wait(bars + 8 * (B_A + wg), 0);
    TM(33 + wg * 16);
#pragma unroll
    for (int k = 0; k < 36; k++) ldsm4t(a[4 * k], a[4 * k + 1], a[4 * k + 2], a[4 * k + 3], reg + lma + k * 2048);
    float r0, r1;
    {
      const float p0 = __shfl_sync(~0u, blo(a[0]), lane & ~3), p1 = __shfl_sync(~0u, blo(a[1]), lane & ~3);
      float s0 = 0, s1 = 0, q0 = 0, q1 = 0;
#pragma unroll
      for (int i = 0; i < 72; i++) { float x = blo(a[2 * i]) - p0, y = bhi(a[2 * i]) - p0, z = blo(a[2 * i + 1]) - p1, u = bhi(a[2 * i + 1]) - p1;
        s0 += x + y; s1 += z + u; q0 = fmaf(x, x, q0); q0 = fmaf(y, y, q0); q1 = fmaf(z, z, q1); q1 = fmaf(u, u, q1); }
#pragma unroll
      for (int o = 1; o < 4; o <<= 1) { s0 += __shfl_xor_sync(~0u, s0, o); s1 += __shfl_xor_sync(~0u, s1, o); q0 += __shfl_xor_sync(~0u, q0, o); q1 += __shfl_xor_sync(~0u, q1, o); }
      s0 *= (1.f / D_); s1 *= (1.f / D_);
      r0 = rsqrtf(fmaxf(fmaf(-s0, s0, q0 * (1.f / D_)), 0.f) + 1e-5f); r1 = rsqrtf(fmaxf(fmaf(-s1, s1, q1 * (1.f / D_)), 0.f) + 1e-5f);
      const uint32_t n0 = pack(s0 + p0, s0 + p0), n1 = pack(s1 + p1, s1 + p1);
#pragma unroll
      for (int i = 0; i < 144; i++) asm("sub.rn.bf16x2 %0, %0, %1;" : "+r"(a[i]) : "r"((i & 1) ? n1 : n0));
    }
    float d0[32], d1[32];
    uint32_t park = reg + tl * 16, ba = sb + M_BIAS + t4 * 8;
    mbar_wait(bars + 8 * B_FULL, 0);
    TM(34 + wg * 16);
    chunk1<false>(d0, d1, a, bars, 0, park, ba, leader, r0, r1);
#pragma unroll 1
    for (int c = 0; c < 4; c++) {
      chunk1<true>(d1, d0, a, bars, 1, park, ba, leader, r0, r1);
      chunk1<true>(d0, d1, a, bars, 0, park + 8192, ba + 256, leader, r0, r1);
      park += 16384; ba += 512;
    }
    TM(35 + wg * 16);
    park = reg + tl * 16;
#pragma unroll
    for (int k = 0; k < 32; k++) lds128(a[4 * k], a[4 * k + 1], a[4 * k + 2], a[4 * k + 3], park + k * 2048);
#pragma unroll
    for (int sg = 0; sg < 4; sg++) gelu_slice(&d0[8 * sg], r0, r1, ba + sg * 64, a[128 + 4 * sg], a[129 + 4 * sg], a[130 + 4 * sg], a[131 + 4 * sg]);
    TM(36 + wg * 16);
    const uint4* gin = g_part + ((m * 9 + j) * 8 * 2 + wg) * 512 + tl;
    uint4* gout = g_part + ((m * 9 * 8 + j) * 2 + wg) * 512 + tl;
    uint32_t pi[16];
    auto step2 = [&](auto MODE_, int s) {
      constexpr int MODE = decltype(MODE_)::value;
      const uint32_t ph = (s & 1) ^ 1;
      const uint4* pa = gin + (j ^ (10 - s)) * 1024;
      const uint4* pb = gin + (j ^ (9 - s)) * 1024;
#pragma unroll
      for (int sg = 0; sg < 4; sg++) {
        mma_stage(d0, a, sg);
        if (MODE == 1 && sg < 2) {
          mbar_wait(bars + 8 * B_H, 0);
#pragma unroll
          for (int i = 2 * sg; i < 2 * sg + 2; i++) {
            uint32_t h[4]; ldsm4t(h[0], h[1], h[2], h[3], reg + 7 * 8192 + lma + i * 2048);
            float bb[4];
            asm volatile("ld.shared.v2.f32 {%0,%1}, [%2];" : "=f"(bb[0]), "=f"(bb[1]) : "r"(sb + M_B2 + t4 * 8 + i * 64) : "memory");
            asm volatile("ld.shared.v2.f32 {%0,%1}, [%2];" : "=f"(bb[2]), "=f"(bb[3]) : "r"(sb + M_B2 + t4 * 8 + i * 64 + 32) : "memory");
#pragma unroll
            for (int r = 0; r < 4; r++) { d1[8 * i + 2 * r] = fmaf(blo(h[r]), 2.f, bb[(r >> 1) * 2]); d1[8 * i + 2 * r + 1] = fmaf(bhi(h[r]), 2.f, bb[(r >> 1) * 2 + 1]);
              asm volatile("" : "+f"(d1[8 * i + 2 * r]), "+f"(d1[8 * i + 2 * r + 1])::"memory"); }
          }
        }
        const uint32_t nb = bars + 8 * (B_FULL + ((sg + 1) & 3)), np = sg == 3 ? ph ^ 1 : ph;
        if (MODE >= 2 && sg == 0) { poll_part(pi, pa, tag); add_part<0, 5>(d1, pi); }
        if (MODE >= 2 && sg == 1) { mbar_wait(nb, np); add_part<5, 11>(d1, pi); }
        if (MODE >= 2 && sg == 2) { mbar_wait(nb, np); add_part<11, 16>(d1, pi); }
        if (MODE >= 1 && sg == 2) ld_part(pi, pb);
        if (MODE == 3 && sg == 3) { poll_part(pi, pb, tag); add_part<0, 16>(d1, pi); }
        if (sg < 3 || MODE != 3) mbar_wait(nb, np);
        WG_WAIT0();
        if (leader) mbar_arrive(bars + 8 * (B_EMPTY + sg));
      }
      pin(d0);
      if (MODE != 3) {
        uint4* p = s == 0 ? g_part + ((m * 9 + 8) * 8 + wg * 4 + w) * 1024 + j * 128 + lane : gout + (j ^ (8 - s)) * 8192;
        const int ps = s == 0 ? 32 : 128;
#pragma unroll
        for (int i = 0; i < 4; i++)
          asm volatile("st.relaxed.gpu.global.v4.u32 [%0], {%1,%2,%3,%4};" ::"l"(p + i * ps), "r"((pack(d0[8 * i], d0[8 * i + 1]) & ~1u) | tag), "r"(pack(d0[8 * i + 2], d0[8 * i + 3])),
                       "r"(pack(d0[8 * i + 4], d0[8 * i + 5])), "r"(pack(d0[8 * i + 6], d0[8 * i + 7])) : "memory");
        if (MODE == 0 && lane == 0) mbar_arrive(bars + 8 * (B_STEP + s));
      }
      TM2(wg * 16 + s);
    };
    step2(IC<0>{}, 0); step2(IC<0>{}, 1);
    step2(IC<1>{}, 2);
#pragma unroll 1
    for (int s = 3; s < 8; s++) step2(IC<2>{}, s);
    step2(IC<3>{}, 8);
    TM(37 + wg * 16);
    const uint32_t ob = reg + 7 * 8192 + w * 2048;
    const int op = lane & 15, orow = 8 * ((op >> 1) & 1) + 2 * (op >> 2) + (op & 1);
#pragma unroll
    for (int i = 0; i < 4; i++) {
      uint32_t o[4];
#pragma unroll
      for (int r = 0; r < 4; r++) o[r] = pack(0.5f * (d0[8 * i + 2 * r] + d1[8 * i + 2 * r]), 0.5f * (d0[8 * i + 2 * r + 1] + d1[8 * i + 2 * r + 1]));
      stsm4(ob + orow * 128 + (((2 * i + (lane >> 4)) ^ (orow & 7)) * 16), o[0], o[1], o[2], o[3]);
    }
    TM(38 + wg * 16);
    PROXY_FENCE_SMEM();
    __syncwarp();
    if (elect()) { tma2d_store(&tm_o, ob, j * 64, m * 128 + wg * 64 + w * 16); asm volatile("cp.async.bulk.commit_group;" ::: "memory"); asm volatile("cp.async.bulk.wait_group.read 0;" ::: "memory"); }
    TM(39 + wg * 16);
  }
}

typedef CUresult (*EncFn)(CUtensorMap*, CUtensorMapDataType, cuuint32_t, void*, const cuuint64_t*, const cuuint64_t*, const cuuint32_t*, const cuuint32_t*,
                          CUtensorMapInterleave, CUtensorMapSwizzle, CUtensorMapL2promotion, CUtensorMapFloatOOBfill);
void mk2d(EncFn enc, CUtensorMap* m, void* p, uint64_t inner, uint64_t outer, uint32_t bi, uint32_t bo) {
  cuuint64_t d[2] = {inner, outer}, s[1] = {inner * 2}; cuuint32_t b[2] = {bi, bo}, e[2] = {1, 1};
  enc(m, CU_TENSOR_MAP_DATA_TYPE_BFLOAT16, 2, p, d, s, b, e, CU_TENSOR_MAP_INTERLEAVE_NONE, CU_TENSOR_MAP_SWIZZLE_128B, CU_TENSOR_MAP_L2_PROMOTION_L2_128B, CU_TENSOR_MAP_FLOAT_OOB_FILL_NONE);
}
}

extern "C" void kernel_launch(void* const* d_in, const int* in_sizes, int n_in, void* d_out, int out_size) {
  const uint16_t *q = (const uint16_t*)d_in[0], *k = (const uint16_t*)d_in[1], *v = (const uint16_t*)d_in[2], *sk = (const uint16_t*)d_in[3],
                 *ssk = (const uint16_t*)d_in[4], *Dv = (const uint16_t*)d_in[5], *b1 = (const uint16_t*)d_in[8], *b2 = (const uint16_t*)d_in[10];
  void* f = nullptr; cudaDriverEntryPointQueryResult qr;
  cudaGetDriverEntryPoint("cuTensorMapEncodeTiled", &f, cudaEnableDefault, &qr);
  EncFn enc = (EncFn)f;
  void* hT; cudaGetSymbolAddress(&hT, g_hT);
  CUtensorMap tm_h, tm_w1, tm_w2, tm_o;
  mk2d(enc, &tm_h, hT, S_, D_, 64, 64); mk2d(enc, &tm_w1, d_in[7], F_, D_, 64, 144); mk2d(enc, &tm_w2, d_in[9], D_, F_, 64, 144); mk2d(enc, &tm_o, d_out, D_, S_, 64, 16);
  cudaFuncSetAttribute(k_conv, cudaFuncAttributeMaxDynamicSharedMemorySize, CV_SMEM);
  cudaFuncSetAttribute(k_mlp, cudaFuncAttributeMaxDynamicSharedMemorySize, M_SMEM);
  k_prep<<<128, 288>>>(q, k, v, sk);
  k_conv<<<128, 384, CV_SMEM>>>(ssk, Dv);
  k_mlp<<<128, 384, M_SMEM>>>(tm_h, tm_w1, tm_w2, tm_o, b1, b2, (const uint16_t*)d_in[9], (uint16_t*)d_out);
}
```

```cpp
#include <cuda_runtime.h>
#include <cuda.h>
#include <cuda_bf16.h>
#include <stdint.h>

namespace {
constexpr int S_ = 2048, D_ = 576, F_ = 4608;

__device__ __forceinline__ uint32_t s2u(const void* p) { return (uint32_t)__cvta_generic_to_shared(p); }
__device__ __forceinline__ uint64_t mkdesc(uint32_t addr, uint32_t lbo, uint32_t sbo, int sw) {
  return (uint64_t)((addr & 0x3FFFF) >> 4) | ((uint64_t)(lbo >> 4) << 16) | ((uint64_t)(sbo >> 4) << 32) | ((uint64_t)sw << 62);
}
__device__ __forceinline__ void mbar_init(uint32_t b, int c) { asm volatile("mbarrier.init.shared::cta.b64 [%0], %1;" ::"r"(b), "r"(c)); }
__device__ __forceinline__ void mbar_expect(uint32_t b, uint32_t tx) { asm volatile("mbarrier.arrive.expect_tx.shared::cta.b64 _, [%0], %1;" ::"r"(b), "r"(tx) : "memory"); }
__device__ __forceinline__ void mbar_arrive(uint32_t b) { asm volatile("mbarrier.arrive.shared::cta.b64 _, [%0];" ::"r"(b) : "memory"); }
__device__ __forceinline__ void mbar_wait(uint32_t b, uint32_t ph) {
  asm volatile("{\n.reg .pred p;\n.reg .u32 n;\nmbarrier.try_wait.parity.shared::cta.b64 p, [%0], %1;\n@p bra LD;\nmov.u32 n, %%clock;\nand.b32 n, n, 7;\n"
               "LW:\nmbarrier.try_wait.parity.shared::cta.b64 p, [%0], %1;\n@p bra LD;\n"
               "add.u32 n, n, 1;\nsetp.lt.u32 p, n, 20000;\n@p bra LW;\nLD:\n}" ::"r"(b), "r"(ph) : "memory");
}
__device__ __forceinline__ void mbar_wait_long(uint32_t b, uint32_t ph) {
  asm volatile("{\n.reg .pred p;\n.reg .u32 n;\nmov.u32 n, 0;\nLW:\nmbarrier.test_wait.parity.shared::cta.b64 p, [%0], %1;\n@p bra LD;\nnanosleep.u32 200;\n"
               "add.u32 n, n, 1;\nsetp.lt.u32 p, n, 10000;\n@p bra LW;\nLD:\n}" ::"r"(b), "r"(ph) : "memory");
}
__device__ __forceinline__ void sched_fence(uint32_t b) {
  asm volatile("{\n.reg .pred p;\nmbarrier.test_wait.parity.shared::cta.b64 p, [%0], 0;\n@p bra LD;\nnanosleep.u32 0;\nLD:\n}" ::"r"(b) : "memory");
}
__device__ __forceinline__ void flag_wait(const unsigned* p, unsigned target) {
  asm volatile("{\n.reg .pred p;\n.reg .u32 n, v;\nmov.u32 n, 0;\nLW:\nld.acquire.gpu.global.u32 v, [%0];\nsetp.ge.u32 p, v, %1;\n@p bra LD;\n"
               "add.u32 n, n, 1;\nsetp.lt.u32 p, n, 2000000;\n@p bra LW;\nLD:\n}" ::"l"(p), "r"(target) : "memory");
}
__device__ __forceinline__ void tma2d(uint32_t dst, const CUtensorMap* m, int c0, int c1, uint32_t bar) {
  asm volatile("cp.async.bulk.tensor.2d.shared::cluster.global.mbarrier::complete_tx::bytes [%0], [%1, {%3, %4}], [%2];" ::"r"(dst), "l"(m), "r"(bar), "r"(c0), "r"(c1) : "memory");
}
__device__ __forceinline__ void tma2d_store(const CUtensorMap* m, uint32_t src, int c0, int c1) {
  asm volatile("cp.async.bulk.tensor.2d.global.shared::cta.bulk_group [%0, {%2, %3}], [%1];" ::"l"(m), "r"(src), "r"(c0), "r"(c1) : "memory");
}
__device__ __forceinline__ void bulk_load(uint32_t dst, const void* src, uint32_t bytes, uint32_t bar) {
  asm volatile("cp.async.bulk.shared::cluster.global.mbarrier::complete_tx::bytes [%0], [%1], %2, [%3];" ::"r"(dst), "l"(src), "r"(bytes), "r"(bar) : "memory");
}
__device__ __forceinline__ void bulk_store(void* dst, uint32_t src, uint32_t bytes) {
  asm volatile("cp.async.bulk.global.shared::cta.bulk_group [%0], [%1], %2;" ::"l"(dst), "r"(src), "r"(bytes) : "memory");
}
__device__ __forceinline__ void l2_prefetch(const void* p, uint32_t bytes) { asm volatile("cp.async.bulk.prefetch.L2.global [%0], %1;" ::"l"(p), "r"(bytes) : "memory"); }
__device__ __forceinline__ void mma16816(float (&d)[4], const uint32_t* a, uint32_t b0, uint32_t b1) {
  asm("mma.sync.aligned.m16n8k16.row.col.f32.bf16.bf16.f32 {%0,%1,%2,%3}, {%4,%5,%6,%7}, {%8,%9}, {%0,%1,%2,%3};"
      : "+f"(d[0]), "+f"(d[1]), "+f"(d[2]), "+f"(d[3]) : "r"(a[0]), "r"(a[1]), "r"(a[2]), "r"(a[3]), "r"(b0), "r"(b1));
}
__device__ __forceinline__ void mma1688(float (&d)[4], uint32_t a0, uint32_t a1, uint32_t b0) {
  asm("mma.sync.aligned.m16n8k8.row.col.f32.bf16.bf16.f32 {%0,%1,%2,%3}, {%4,%5}, {%6}, {%0,%1,%2,%3};"
      : "+f"(d[0]), "+f"(d[1]), "+f"(d[2]), "+f"(d[3]) : "r"(a0), "r"(a1), "r"(b0));
}
__device__ __forceinline__ bool elect() { uint32_t p; asm volatile("{.reg .pred p; elect.sync _|p, 0xffffffff; selp.b32 %0,1,0,p;}" : "=r"(p)); return p; }
__device__ __forceinline__ uint32_t pack(float lo, float hi) { uint32_t r; asm("cvt.rn.bf16x2.f32 %0,%1,%2;" : "=r"(r) : "f"(hi), "f"(lo)); return r; }
__device__ __forceinline__ float blo(uint32_t v) { return __uint_as_float(v << 16); }
__device__ __forceinline__ float bhi(uint32_t v) { return __uint_as_float(v & 0xffff0000u); }
__device__ __forceinline__ void lds128(uint32_t& a, uint32_t& b, uint32_t& c, uint32_t& d, uint32_t addr) {
  asm volatile("ld.shared.v4.b32 {%0,%1,%2,%3}, [%4];" : "=r"(a), "=r"(b), "=r"(c), "=r"(d) : "r"(addr) : "memory");
}
__device__ __forceinline__ void sts128(uint32_t addr, uint32_t a, uint32_t b, uint32_t c, uint32_t d) {
  asm volatile("st.shared.v4.b32 [%0], {%1,%2,%3,%4};" ::"r"(addr), "r"(a), "r"(b), "r"(c), "r"(d) : "memory");
}
__device__ __forceinline__ void ldsm4t(uint32_t& a, uint32_t& b, uint32_t& c, uint32_t& d, uint32_t addr) {
  asm volatile("ldmatrix.sync.aligned.m8n8.x4.trans.shared.b16 {%0,%1,%2,%3}, [%4];" : "=r"(a), "=r"(b), "=r"(c), "=r"(d) : "r"(addr) : "memory");
}
__device__ __forceinline__ void ldsm4(uint32_t& a, uint32_t& b, uint32_t& c, uint32_t& d, uint32_t addr) {
  asm volatile("ldmatrix.sync.aligned.m8n8.x4.shared.b16 {%0,%1,%2,%3}, [%4];" : "=r"(a), "=r"(b), "=r"(c), "=r"(d) : "r"(addr) : "memory");
}
__device__ __forceinline__ void stsm4(uint32_t addr, uint32_t a, uint32_t b, uint32_t c, uint32_t d) {
  asm volatile("stmatrix.sync.aligned.m8n8.x4.shared.b16 [%0], {%1,%2,%3,%4};" ::"r"(addr), "r"(a), "r"(b), "r"(c), "r"(d) : "memory");
}
__device__ __forceinline__ void nbar_sync(int id, int n) { asm volatile("bar.sync %0, %1;" ::"r"(id), "r"(n) : "memory"); }
__device__ __forceinline__ void nbar_arrive(int id, int n) { asm volatile("bar.arrive %0, %1;" ::"r"(id), "r"(n) : "memory"); }
#define WG_FENCE() asm volatile("wgmma.fence.sync.aligned;" ::: "memory")
#define WG_COMMIT() asm volatile("wgmma.commit_group.sync.aligned;" ::: "memory")
#define WG_WAIT0() asm volatile("wgmma.wait_group.sync.aligned 0;" ::: "memory")
#define WG_WAIT1() asm volatile("wgmma.wait_group.sync.aligned 1;" ::: "memory")
#define PROXY_FENCE_SMEM() asm volatile("fence.proxy.async.shared::cta;" ::: "memory")
#define PROXY_FENCE_ALL() asm volatile("fence.proxy.async;" ::: "memory")
template <int N> __device__ __forceinline__ void pin(float (&d)[N]) {
#pragma unroll
  for (int i = 0; i < N; i++) asm volatile("" : "+f"(d[i])::"memory");
}
__device__ __forceinline__ void wg64t(float (&d)[32], const uint32_t* a, uint64_t db) {
  asm volatile("wgmma.mma_async.sync.aligned.m64n64k16.f32.bf16.bf16 {%0, %1, %2, %3, %4, %5, %6, %7, %8, %9, %10, %11, %12, %13, %14, %15, %16, %17, %18, %19, %20, %21, %22, %23, %24, %25, %26, %27, %28, %29, %30, %31}, {%32, %33, %34, %35}, %36, 1, 1, 1, 1;"
    : "+f"(d[0]), "+f"(d[1]), "+f"(d[2]), "+f"(d[3]), "+f"(d[4]), "+f"(d[5]), "+f"(d[6]), "+f"(d[7]), "+f"(d[8]), "+f"(d[9]), "+f"(d[10]), "+f"(d[11]), "+f"(d[12]), "+f"(d[13]), "+f"(d[14]), "+f"(d[15]), "+f"(d[16]), "+f"(d[17]), "+f"(d[18]), "+f"(d[19]), "+f"(d[20]), "+f"(d[21]), "+f"(d[22]), "+f"(d[23]), "+f"(d[24]), "+f"(d[25]), "+f"(d[26]), "+f"(d[27]), "+f"(d[28]), "+f"(d[29]), "+f"(d[30]), "+f"(d[31])
    : "r"(a[0]), "r"(a[1]), "r"(a[2]), "r"(a[3]), "l"(db));
}
__device__ __forceinline__ void wg64tz(float (&d)[32], const uint32_t* a, uint64_t db) {
  asm volatile("wgmma.mma_async.sync.aligned.m64n64k16.f32.bf16.bf16 {%0, %1, %2, %3, %4, %5, %6, %7, %8, %9, %10, %11, %12, %13, %14, %15, %16, %17, %18, %19, %20, %21, %22, %23, %24, %25, %26, %27, %28, %29, %30, %31}, {%32, %33, %34, %35}, %36, 0, 1, 1, 1;"
    : "=f"(d[0]), "=f"(d[1]), "=f"(d[2]), "=f"(d[3]), "=f"(d[4]), "=f"(d[5]), "=f"(d[6]), "=f"(d[7]), "=f"(d[8]), "=f"(d[9]), "=f"(d[10]), "=f"(d[11]), "=f"(d[12]), "=f"(d[13]), "=f"(d[14]), "=f"(d[15]), "=f"(d[16]), "=f"(d[17]), "=f"(d[18]), "=f"(d[19]), "=f"(d[20]), "=f"(d[21]), "=f"(d[22]), "=f"(d[23]), "=f"(d[24]), "=f"(d[25]), "=f"(d[26]), "=f"(d[27]), "=f"(d[28]), "=f"(d[29]), "=f"(d[30]), "=f"(d[31])
    : "r"(a[0]), "r"(a[1]), "r"(a[2]), "r"(a[3]), "l"(db));
}
__device__ __forceinline__ void wg64(float (&d)[32], const uint32_t* a, uint64_t db) {
  asm volatile("wgmma.mma_async.sync.aligned.m64n64k16.f32.bf16.bf16 {%0, %1, %2, %3, %4, %5, %6, %7, %8, %9, %10, %11, %12, %13, %14, %15, %16, %17, %18, %19, %20, %21, %22, %23, %24, %25, %26, %27, %28, %29, %30, %31}, {%32, %33, %34, %35}, %36, 1, 1, 1, 0;"
    : "+f"(d[0]), "+f"(d[1]), "+f"(d[2]), "+f"(d[3]), "+f"(d[4]), "+f"(d[5]), "+f"(d[6]), "+f"(d[7]), "+f"(d[8]), "+f"(d[9]), "+f"(d[10]), "+f"(d[11]), "+f"(d[12]), "+f"(d[13]), "+f"(d[14]), "+f"(d[15]), "+f"(d[16]), "+f"(d[17]), "+f"(d[18]), "+f"(d[19]), "+f"(d[20]), "+f"(d[21]), "+f"(d[22]), "+f"(d[23]), "+f"(d[24]), "+f"(d[25]), "+f"(d[26]), "+f"(d[27]), "+f"(d[28]), "+f"(d[29]), "+f"(d[30]), "+f"(d[31])
    : "r"(a[0]), "r"(a[1]), "r"(a[2]), "r"(a[3]), "l"(db));
}
__device__ __forceinline__ void wg64z(float (&d)[32], const uint32_t* a, uint64_t db) {
  asm volatile("wgmma.mma_async.sync.aligned.m64n64k16.f32.bf16.bf16 {%0, %1, %2, %3, %4, %5, %6, %7, %8, %9, %10, %11, %12, %13, %14, %15, %16, %17, %18, %19, %20, %21, %22, %23, %24, %25, %26, %27, %28, %29, %30, %31}, {%32, %33, %34, %35}, %36, 0, 1, 1, 0;"
    : "=f"(d[0]), "=f"(d[1]), "=f"(d[2]), "=f"(d[3]), "=f"(d[4]), "=f"(d[5]), "=f"(d[6]), "=f"(d[7]), "=f"(d[8]), "=f"(d[9]), "=f"(d[10]), "=f"(d[11]), "=f"(d[12]), "=f"(d[13]), "=f"(d[14]), "=f"(d[15]), "=f"(d[16]), "=f"(d[17]), "=f"(d[18]), "=f"(d[19]), "=f"(d[20]), "=f"(d[21]), "=f"(d[22]), "=f"(d[23]), "=f"(d[24]), "=f"(d[25]), "=f"(d[26]), "=f"(d[27]), "=f"(d[28]), "=f"(d[29]), "=f"(d[30]), "=f"(d[31])
    : "r"(a[0]), "r"(a[1]), "r"(a[2]), "r"(a[3]), "l"(db));
}
__device__ __forceinline__ void wg32(float (&d)[16], const uint32_t* a, uint64_t db) {
  asm volatile("wgmma.mma_async.sync.aligned.m64n32k16.f32.bf16.bf16 {%0, %1, %2, %3, %4, %5, %6, %7, %8, %9, %10, %11, %12, %13, %14, %15}, {%16, %17, %18, %19}, %20, 1, 1, 1, 0;"
    : "+f"(d[0]), "+f"(d[1]), "+f"(d[2]), "+f"(d[3]), "+f"(d[4]), "+f"(d[5]), "+f"(d[6]), "+f"(d[7]), "+f"(d[8]), "+f"(d[9]), "+f"(d[10]), "+f"(d[11]), "+f"(d[12]), "+f"(d[13]), "+f"(d[14]), "+f"(d[15])
    : "r"(a[0]), "r"(a[1]), "r"(a[2]), "r"(a[3]), "l"(db));
}
__device__ __forceinline__ void wg32z(float (&d)[16], const uint32_t* a, uint64_t db) {
  asm volatile("wgmma.mma_async.sync.aligned.m64n32k16.f32.bf16.bf16 {%0, %1, %2, %3, %4, %5, %6, %7, %8, %9, %10, %11, %12, %13, %14, %15}, {%16, %17, %18, %19}, %20, 0, 1, 1, 0;"
    : "=f"(d[0]), "=f"(d[1]), "=f"(d[2]), "=f"(d[3]), "=f"(d[4]), "=f"(d[5]), "=f"(d[6]), "=f"(d[7]), "=f"(d[8]), "=f"(d[9]), "=f"(d[10]), "=f"(d[11]), "=f"(d[12]), "=f"(d[13]), "=f"(d[14]), "=f"(d[15])
    : "r"(a[0]), "r"(a[1]), "r"(a[2]), "r"(a[3]), "l"(db));
}
}

__device__ __align__(1024) uint16_t g_kvT[D_ * S_];
__device__ __align__(1024) uint16_t g_xT[D_ * S_];
__device__ __align__(1024) uint4 g_st1[512];
__device__ __align__(1024) uint16_t g_hT[2 * D_ * S_];
__device__ __align__(1024) uint4 g_part[16 * 8 * 8 * 1024];
__device__ __align__(1024) unsigned g_cnt[1024 + 1024];
#define TMFLUSH()
#define TC(i)
#define TM(i)
#define TMW(i)

namespace {
constexpr uint32_t SB = 1024;
#define DELAY1 3000
#define DELAY2 2400
#define RSLEEP 60
#define W1PF 1
#define XLATE 1
#define GSPLIT 0
#define NB_ 3
#define HO 3
#define EARLY0 1
#define WARM 0
#define SLATE 0
#define EARLYH 0
#define WEAK 1
#define SSH 21
#define DSH 14
#define STEPMUL 2097152
#define STR2(x) #x
#define STR(x) STR2(x)
template <int V> struct IC { static constexpr int value = V; };

constexpr int ST_B = 144 * 128;
constexpr int M_RING = 0, M_PARK = 4 * ST_B;
constexpr int M_CONST = M_PARK + 18 * 8192;
constexpr int M_BIAS = M_CONST + 4096, M_B2 = M_BIAS + 576 * 4, M_SMALL = M_B2 + 128 * 4, M_STAT = M_SMALL + 128, M_BAR = M_STAT + 512;
constexpr int CV_P = 8320, CV_PL = 4992, CV_YW = 4224, CV_Y = 4 * CV_YW, XP = 1168, KV_H = 19 * 1152 + 64;
constexpr int C_X = M_RING, C_SK = C_X + 16 * XP, C_KV = C_SK + 4608;
constexpr int C_KVO = M_PARK, C_XO = C_KVO + 5 * 2048, C_P2 = C_XO + 576 * 32, C_PL0 = C_P2 + 2 * CV_P;
constexpr int C_PL1 = M_PARK + 8 * 8192, C_P4 = C_PL1 + 4 * CV_PL;
constexpr int C_PL4 = M_PARK + 12 * 8192, C_Y = C_PL4 + 2 * CV_PL, C_P0 = C_Y + CV_Y;
__device__ __forceinline__ int plane_of(int it) { return it == 4 ? C_PL4 : ((it & 1) ? C_PL1 : C_PL0) + (it >> 1) * 2 * CV_PL; }
__device__ __forceinline__ int pairs_of(int it) { return it == 4 ? C_P4 : (it < 2 ? C_P0 : C_P2) + (it & 1) * CV_P; }
enum { B_FULL = 0, B_EMPTY = 4, B_HINT = 16, B_PL = 23, B_YF = 24, B_YE = 28, B_STEP = 30, B_H = 31, B_SLAB = 32, B_PEER = 33, B_RDY = 35, B_A = 36,
       B_X = 41, B_KV = 42, B_RE = 43, B_KA = 44, B_NB = 45 };
enum Cnt { N_KVA = 0, N_KVB, N_X, N_F, N_H, N_CNT = N_H + 5 };
static_assert(C_KV + 2 * KV_H <= M_PARK && C_PL0 + 4 * CV_PL <= C_PL1 && C_P4 + CV_P <= C_PL4 && C_Y + 2 * CV_Y <= M_CONST && 2 * CV_P <= CV_Y && C_PL0 % 128 == 0 && C_XO % 128 == 0, "smem map");
constexpr int M_TM = M_BAR + B_NB * 8, M_SMEM = M_TM + 768;
constexpr uint32_t PEER = 0x1000000u;

__device__ __forceinline__ void grid_arrive(unsigned* c) { asm volatile("red.release.gpu.global.add.u32 [%0], 1;" ::"l"(c) : "memory"); }
__device__ __forceinline__ void grid_wait(const unsigned* p, unsigned target) {
  asm volatile("{\n.reg .pred p;\n.reg .u32 n, v;\n.reg .s32 d;\nmov.u32 n, 0;\nLW:\nld.relaxed.gpu.global.u32 v, [%0];\nsub.s32 d, v, %1;\nsetp.ge.s32 p, d, 0;\n@p bra LD;\n"
               "add.u32 n, n, 1;\nsetp.lt.u32 p, n, 20000;\n@p bra LW;\nLD:\nfence.acquire.gpu;\nfence.proxy.async.global;\n}" ::"l"(p), "r"(target) : "memory");
}

__device__ __forceinline__ void hint_wait(const unsigned* p, unsigned target) {
  asm volatile("{\n.reg .pred p;\n.reg .u32 n, v;\n.reg .s32 d;\nmov.u32 n, 0;\nLW:\nld.relaxed.gpu.global.u32 v, [%0];\nsub.s32 d, v, %1;\nsetp.ge.s32 p, d, 0;\n@p bra LD;\n"
               "add.u32 n, n, 1;\nsetp.lt.u32 p, n, 20000;\n@p bra LW;\nLD:\n}" ::"l"(p), "r"(target) : "memory");
}

__device__ __forceinline__ bool hint_try(const unsigned* p, unsigned target, uint32_t bar, uint32_t ph) {
  uint32_t ok;
  asm volatile("{\n.reg .pred p;\n.reg .u32 n, v;\n.reg .s32 d;\nmov.u32 n, 0;\nLW:\nld.relaxed.gpu.global.u32 v, [%1];\nsub.s32 d, v, %2;\nsetp.ge.s32 p, d, 0;\nselp.u32 %0, 1, 0, p;\n@p bra LD;\n"
               "mbarrier.test_wait.parity.shared::cta.b64 p, [%3], %4;\n@p bra LD;\nadd.u32 n, n, 1;\nsetp.lt.u32 p, n, 20000;\n@p bra LW;\nLD:\n}" : "=r"(ok) : "l"(p), "r"(target), "r"(bar), "r"(ph) : "memory");
  return __all_sync(~0u, ok);
}
template <bool STRONG> __device__ __forceinline__ uint4 ld16(const uint4* p) {
  uint4 v;
  if (STRONG) asm volatile("ld.relaxed.gpu.global.v4.u32 {%0,%1,%2,%3}, [%4];" : "=r"(v.x), "=r"(v.y), "=r"(v.z), "=r"(v.w) : "l"(p) : "memory");
  else asm volatile("ld.global.L1::no_allocate.v4.u32 {%0,%1,%2,%3}, [%4];" : "=r"(v.x), "=r"(v.y), "=r"(v.z), "=r"(v.w) : "l"(p) : "memory");
  return v;
}
__device__ __forceinline__ void hint_add(unsigned* p, unsigned v) { asm volatile("red.relaxed.gpu.global.add.u32 [%0], %1;" ::"l"(p), "r"(v) : "memory"); }
__device__ __forceinline__ uint2 ld_relaxed(const uint2* p) { uint2 v; asm volatile("ld.relaxed.gpu.global.v2.u32 {%0,%1}, [%2];" : "=r"(v.x), "=r"(v.y) : "l"(p) : "memory"); return v; }
__device__ __forceinline__ uint4 ld_relaxed(const uint4* p) { uint4 v; asm volatile("ld.relaxed.gpu.global.v4.u32 {%0,%1,%2,%3}, [%4];" : "=r"(v.x), "=r"(v.y), "=r"(v.z), "=r"(v.w) : "l"(p) : "memory"); return v; }
__device__ __forceinline__ uint32_t bmul(uint32_t a, uint32_t b) { uint32_t r; asm("mul.rn.bf16x2 %0, %1, %2;" : "=r"(r) : "r"(a), "r"(b)); return r; }
__device__ __forceinline__ uint32_t badd(uint32_t a, uint32_t b) { uint32_t r; asm("add.rn.bf16x2 %0, %1, %2;" : "=r"(r) : "r"(a), "r"(b)); return r; }
__device__ __forceinline__ uint32_t bneg(uint32_t a) { uint32_t r; asm("neg.bf16x2 %0, %1;" : "=r"(r) : "r"(a)); return r; }
__device__ __forceinline__ uint32_t bfma(uint32_t a, uint32_t b, uint32_t c) { uint32_t r; asm("fma.rn.bf16x2 %0, %1, %2, %3;" : "=r"(r) : "r"(a), "r"(b), "r"(c)); return r; }
template <bool STRONG = !WEAK> __device__ __forceinline__ void kv_fetch(uint32_t (&u)[8], const uint16_t* p) {
  const uint4 x = ld16<STRONG>((const uint4*)p), y = ld16<STRONG>((const uint4*)(p + 1024));
  u[0] = x.x; u[1] = x.y; u[2] = x.z; u[3] = x.w; u[4] = y.x; u[5] = y.y; u[6] = y.z; u[7] = y.w;
}
__device__ __forceinline__ void kv_place(uint32_t (&u)[8], const uint16_t* p, uint32_t dst) {
  for (int n = 0; (u[0] < 0x10000u || u[4] < 0x10000u) && n < 5000; n++) kv_fetch<true>(u, p);
  __syncwarp();
  u[0] ^= 0xffff0000u; u[4] ^= 0xffff0000u;
  sts128(dst + 16, u[0], u[1], u[2], u[3]); sts128(dst + CV_PL, u[0], u[1], u[2], u[3]);
  sts128(dst + 2048 + 16, u[4], u[5], u[6], u[7]); sts128(dst + 2048 + CV_PL, u[4], u[5], u[6], u[7]);
}

__device__ __forceinline__ void tma3d(uint32_t dst, const CUtensorMap* m, int c0, int c1, int c2, uint32_t bar) {
  asm volatile("cp.async.bulk.tensor.3d.shared::cluster.global.mbarrier::complete_tx::bytes [%0], [%1, {%3, %4, %5}], [%2];" ::"r"(dst), "l"(m), "r"(bar), "r"(c0), "r"(c1), "r"(c2) : "memory");
}
__device__ __forceinline__ int fresh_tid() { int v; asm volatile("mov.u32 %0, %%tid.x;" : "=r"(v)); return v; }
__device__ __forceinline__ int fresh_bid() { int v; asm volatile("mov.u32 %0, %%ctaid.x;" : "=r"(v)); return v; }
template <int M0, int M1> __device__ __forceinline__ void conv_lda(uint32_t* a, uint32_t pa) {
#pragma unroll
  for (int m = M0; m < M1; m++)
#pragma unroll
    for (int r = 0; r < 4; r++) asm volatile("ld.shared.b32 %0, [%1];" : "=r"(a[4 * m + r]) : "r"(pa + (128 * m + 64 * (r & 1) - 8 * (r >> 1)) * 4) : "memory");
}
template <int C> __device__ __forceinline__ void conv_mma(float (&d)[32], const uint32_t* a, uint64_t db) {
  wg64z(d, a, db + 64 * C);
#pragma unroll
  for (int m = 1; m < 4 * (C + 1); m++) wg64(d, a + 4 * m, db + (64 * C - 16 * m));
}
template <int C> __device__ __forceinline__ void conv_out(const float (&d)[32], float& c0, float& c1, uint32_t ya) {
  uint32_t o[8];
#pragma unroll
  for (int n = 0; n < 8; n++) o[n] = pack(d[4 * n] + (n ? d[4 * n - 2] : c0), d[4 * n + 1] + (n ? d[4 * n - 1] : c1));
  asm volatile("add.f32 %0, %1, 0f80000000;" : "=f"(c0) : "f"(d[30])); asm volatile("add.f32 %0, %1, 0f80000000;" : "=f"(c1) : "f"(d[31]));
#pragma unroll
  for (int i = 0; i < 2; i++)
    asm volatile("stmatrix.sync.aligned.m8n8.x4.trans.shared.b16 [%0], {%1,%2,%3,%4};" ::"r"(ya + C * 1024 + i * 512), "r"(o[4 * i]), "r"(o[4 * i + 1]), "r"(o[4 * i + 2]), "r"(o[4 * i + 3]) : "memory");
}
__device__ __forceinline__ void ssk_fetch(uint32_t (&kq)[12], const uint16_t* row, int t) {
  const uint16_t* src = row + t * 4;
#pragma unroll
  for (int e = 0; e < 4; e++) { asm volatile("ld.global.nc.v2.u32 {%0,%1}, [%2];" : "=r"(kq[2 * e]), "=r"(kq[2 * e + 1]) : "l"(src + e * 512));
    asm volatile("ld.global.nc.u32 %0, [%1];" : "=r"(kq[8 + e]) : "l"(src + e * 512 - ((e == 0 && t == 0) ? 0 : 2))); }
}
__device__ __forceinline__ void build_pairs(uint32_t (&kq)[12], uint32_t dst, int t, float dskip) {
  if (t == 0) { kq[0] = (kq[0] & 0xffff0000u) | (pack(blo(kq[0]) + dskip, 0.f) & 0xffffu); kq[8] = 0; }
  if (t < 2) sts128(dst + t * 16, 0, 0, 0, 0);
#pragma unroll
  for (int e = 0; e < 4; e++) { const uint32_t x = kq[2 * e], y = kq[2 * e + 1];
    sts128(dst + 32 + e * 2048 + t * 16, __byte_perm(x, kq[8 + e], 0x7610), __byte_perm(x, x, 0x1032), __byte_perm(y, x, 0x7610), __byte_perm(y, y, 0x1032)); }
}

__device__ __forceinline__ float gelu2(float x) {
  float u = x * fmaf(x * x, 8.f * 0.035677408136f, 2.f * 0.7978845608f), t;
  asm("tanh.approx.f32 %0,%1;" : "=f"(t) : "f"(u));
  return fmaf(x, t, x);
}
__device__ __forceinline__ void ld_bias(float (&bv)[4], uint32_t ba) {
  asm volatile("ld.shared.v2.f32 {%0,%1}, [%2];" : "=f"(bv[0]), "=f"(bv[1]) : "r"(ba) : "memory");
  asm volatile("ld.shared.v2.f32 {%0,%1}, [%2];" : "=f"(bv[2]), "=f"(bv[3]) : "r"(ba + 32) : "memory");
}
__device__ __forceinline__ void gelu_slice(const float* e, float r0, float r1, float (&bv)[4], uint32_t nba, uint32_t& p0, uint32_t& p1, uint32_t& p2, uint32_t& p3) {
  const float x0 = fmaf(e[0], r0, bv[0]), x1 = fmaf(e[1], r0, bv[1]), x2 = fmaf(e[2], r1, bv[0]), x3 = fmaf(e[3], r1, bv[1]);
  const float x4 = fmaf(e[4], r0, bv[2]), x5 = fmaf(e[5], r0, bv[3]), x6 = fmaf(e[6], r1, bv[2]), x7 = fmaf(e[7], r1, bv[3]);
  ld_bias(bv, nba);
  p0 = pack(gelu2(x0), gelu2(x1)); p1 = pack(gelu2(x2), gelu2(x3)); p2 = pack(gelu2(x4), gelu2(x5)); p3 = pack(gelu2(x6), gelu2(x7));
}
template <int K0, int K1> __device__ __forceinline__ void unpark(uint32_t (&a)[144], uint32_t park0, bool on) {
#pragma unroll
  for (int k = K0; k < K1; k++)
    asm volatile("{.reg .pred p; setp.ne.u32 p, %5, 0; @p ld.shared.v4.b32 {%0,%1,%2,%3}, [%4];}" : "+r"(a[4 * k]), "+r"(a[4 * k + 1]), "+r"(a[4 * k + 2]), "+r"(a[4 * k + 3])
                 : "r"(park0 + (k >> 2) * 16384 + (k & 3) * 2048), "r"((uint32_t)on) : "memory");
}
template <int N0, int N1, int K0, int K1> __device__ __forceinline__ void gelu_last(const float (&e)[32], float r0, float r1, uint32_t ba, uint32_t (&a)[144], uint32_t park0) {
  float bv[6];
#pragma unroll
  for (int n = N0; n < N1; n++) asm volatile("ld.shared.v2.f32 {%0,%1}, [%2];" : "=f"(bv[2 * (n - N0)]), "=f"(bv[2 * (n - N0) + 1]) : "r"(ba + n * 32) : "memory");
  unpark<K0, K1>(a, park0, true);
#pragma unroll
  for (int n = N0; n < N1; n++) { const float b0 = bv[2 * (n - N0)], b1 = bv[2 * (n - N0) + 1];
    a[128 + 2 * n] = pack(gelu2(fmaf(e[4 * n], r0, b0)), gelu2(fmaf(e[4 * n + 1], r0, b1))); a[129 + 2 * n] = pack(gelu2(fmaf(e[4 * n + 2], r1, b0)), gelu2(fmaf(e[4 * n + 3], r1, b1)));
    asm volatile("" : "+r"(a[128 + 2 * n]), "+r"(a[129 + 2 * n])::"memory"); }
}
__device__ __forceinline__ void mma_stage(float (&d)[32], const uint32_t (&a)[144], int sg, uint32_t buf16 = 0) {
  const uint64_t db = mkdesc(SB + M_RING + sg * ST_B, 16384, 1024, 1) + buf16;
  WG_FENCE();
#pragma unroll
  for (int u = 0; u < 9; u++) { if ((sg | u) == 0) wg64tz(d, &a[0], db); else wg64t(d, &a[(sg * 9 + u) * 4], db + u * 128); }
  WG_COMMIT();
}
__device__ __forceinline__ void mma_half(float (&d)[32], const uint32_t (&a)[144], int hf, uint32_t buf16) {
  const uint64_t db = mkdesc(SB + M_RING + hf * 2 * ST_B, 16384, 1024, 1) + buf16;
  WG_FENCE();
#pragma unroll
  for (int u = 0; u < 18; u++) { if ((hf | u) == 0) wg64tz(d, &a[0], db); else wg64t(d, &a[(hf * 18 + u) * 4], db + u * 128); }
  WG_COMMIT();
}
template <int I0> __device__ __forceinline__ void center(uint32_t (&a)[144], uint32_t n0, uint32_t n1) {
#pragma unroll
  for (int i = I0; i < I0 + 36; i++) asm volatile("sub.rn.bf16x2 %0, %0, %1;" : "+r"(a[i]) : "r"((i & 1) ? n1 : n0));
}
template <bool MAYBE_LAST> __device__ __forceinline__ void chunk1(bool last, float (&d)[32], float (&e)[32], uint32_t (&a)[144], uint32_t bars, uint32_t ph, uint32_t park, uint32_t ba,
                                                                  bool leader, float r0, float r1, float (&bv)[4]) {
#pragma unroll
  for (int sg = 0; sg < 4; sg++) {
    mma_stage(d, a, sg);
    mbar_wait(bars + 8 * (B_FULL + ((sg + 1) & 3)), sg == 3 ? ph ^ 1 : ph);
    if (MAYBE_LAST) { if (sg == 1) unpark<4, 8>(a, park - 7 * 16384, last); if (sg == 2) unpark<8, 13>(a, park - 7 * 16384, last); if (sg == 3) unpark<13, 18>(a, park - 7 * 16384, last); }
    uint32_t p0, p1, p2, p3; gelu_slice(&e[8 * sg], r0, r1, bv, ba + sg * 64 + 64, p0, p1, p2, p3); sts128(park + sg * 2048, p0, p1, p2, p3);
    WG_WAIT0();
    if (leader) mbar_arrive(bars + 8 * (B_EMPTY + sg));
    if (MAYBE_LAST && sg == 0) unpark<0, 4>(a, park - 7 * 16384, last);
  }
  pin(d);
}
__device__ __forceinline__ void ld_part(uint32_t (&u)[16], const char* p) {
#pragma unroll
  for (int i = 0; i < 4; i++) asm volatile("ld.relaxed.gpu.global.v4.u32 {%0,%1,%2,%3}, [%4];" : "=r"(u[4 * i]), "=r"(u[4 * i + 1]), "=r"(u[4 * i + 2]), "=r"(u[4 * i + 3]) : "l"(p + i * 512) : "memory");
}
__device__ __forceinline__ void poll_part(uint32_t (&u)[16], const void* base, uint32_t off, uint32_t step, uint32_t tag) {
  asm volatile("{\n.reg .pred p;\n.reg .u32 n, t, r;\n.reg .u64 a;\nmov.u32 n, 0;\nLW:\nlop3.b32 t, %0, %4, %17, 0x7e;\nlop3.b32 r, %8, %12, %17, 0x7e;\nor.b32 t, t, r;\nand.b32 t, t, 1;\nsetp.eq.u32 p, t, 0;\n@p bra LD;\n"
               "shr.u32 t, n, 31;\nadd.u32 t, t, %19;\nmad.lo.u32 t, t, " STR(STEPMUL) ", %18;\ncvt.u64.u32 a, t;\nadd.u64 a, a, %16;\n"
               "ld.relaxed.gpu.global.v4.u32 {%0,%1,%2,%3}, [a];\nld.relaxed.gpu.global.v4.u32 {%4,%5,%6,%7}, [a+512];\n"
               "ld.relaxed.gpu.global.v4.u32 {%8,%9,%10,%11}, [a+1024];\nld.relaxed.gpu.global.v4.u32 {%12,%13,%14,%15}, [a+1536];\n"
               "add.u32 n, n, 1;\nsetp.lt.u32 p, n, 5000;\n@p bra LW;\nLD:\n}"
               : "+r"(u[0]), "+r"(u[1]), "+r"(u[2]), "+r"(u[3]), "+r"(u[4]), "+r"(u[5]), "+r"(u[6]), "+r"(u[7]), "+r"(u[8]), "+r"(u[9]), "+r"(u[10]), "+r"(u[11]),
                 "+r"(u[12]), "+r"(u[13]), "+r"(u[14]), "+r"(u[15]) : "l"(base), "r"(tag), "r"(off), "r"(step) : "memory");
  __syncwarp();
}
template <int I0, int I1> __device__ __forceinline__ void add_part(float (&s)[32], const uint32_t (&u)[16]) {
#pragma unroll
  for (int i = I0; i < I1; i++) { s[2 * i] += blo(u[i]); s[2 * i + 1] += bhi(u[i]); }
#pragma unroll
  for (int i = 2 * I0; i < 2 * I1; i++) asm volatile("" : "+f"(s[i])::"memory");
}

#define FRESH_IDS() const int tid = fresh_tid(), b = fresh_bid(), lane = tid & 31, tl = tid & 127, g = lane >> 2, t4 = lane & 3, m = b >> 3, j = b & 7, odd = b & 1; \
  const int wp = __shfl_sync(~0u, tid >> 5, 0), wg = wp >> 2, w = wp & 3; const uint32_t sb = SB + (odd << 24), bars = sb + M_BAR; \
  auto chan = [&](int it) { return it < 4 ? b + 128 * it : 512 + (b >> 1); }; \
  auto small_val = [&](int i) { uint32_t v; asm volatile("ld.shared.b32 %0, [%1];" : "=r"(v) : "r"(sb + M_SMALL + i * 4) : "memory"); return v; }; \
  (void)tl; (void)g; (void)t4; (void)m; (void)j; (void)wg; (void)w; (void)bars; (void)chan; (void)small_val

#define LOAD_SLICES() const int hrow = ((small_val(N_F) >> 7) & 1) * D_; \
  auto load_slices = [&](int s0, int s1, uint32_t bar) { mbar_expect(bar, (s1 - s0) * 16384); \
    _Pragma("unroll 1") for (int s = s0; s < s1; s++) tma3d(sb + M_PARK + s * 16384, &P.tm_h2, 0, hrow + s * 64, 2 * m, bar); }

struct Params {
  const uint16_t *k, *v, *q, *sk, *ssk, *Dv, *w1, *b1, *w2, *b2;
  uint16_t *out, *kvT, *xT, *hT;
  uint4 *st1, *part; unsigned* cnt; long long* tm;
  CUtensorMap tm_w1, tm_w2, tm_o, tm_x, tm_kv, tm_h2;
};

__global__ void __launch_bounds__(384, 1) __cluster_dims__(2, 1, 1) k_fused(const __grid_constant__ Params P) {
  extern __shared__ __align__(1024) uint8_t smem_raw[];
  const int tid = threadIdx.x, b = blockIdx.x;
  const uint32_t sb = s2u(smem_raw), bars = sb + M_BAR;
  if (sb != SB + ((b & 1) << 24)) return;
  if (tid == 352) {
    mbar_init(bars + 8 * B_KV, 1);
    asm volatile("fence.mbarrier_init.release.cluster;" ::: "memory");
    const int skip = b ? 0 : 3 * 1152;
    const char *kp = (const char*)P.k + (b * 16 - 3) * 1152, *vp = (const char*)P.v + b * 16 * 1152;
    mbar_expect(bars + 8 * B_KV, 38 * 1152 + 4608 - skip);
    bulk_load(sb + C_KV + skip, kp + skip, 11 * 1152 - skip, bars + 8 * B_KV);
    bulk_load(sb + C_KV + KV_H, kp + 8 * 1152, 11 * 1152, bars + 8 * B_KV);
    bulk_load(sb + C_KV + 11 * 1152, vp, 8 * 1152, bars + 8 * B_KV);
    bulk_load(sb + C_KV + KV_H + 11 * 1152, vp + 8 * 1152, 8 * 1152, bars + 8 * B_KV);
    bulk_load(sb + C_SK, P.sk, 4608, bars + 8 * B_KV);
  }
  const uint32_t tstart = (uint32_t)clock();
  const int wp = __shfl_sync(~0u, tid >> 5, 0), wg = wp >> 2, lane = tid & 31;
  const int j = b & 7;
  auto chan = [&](int it) { return it < 4 ? b + 128 * it : 512 + (b >> 1); };
  if (wp == 9 && lane < 6) asm volatile("prefetch.tensormap [%0];" ::"l"(&P.tm_w1 + lane) : "memory");
  TM(wg);
  if (wp < 10 && elect()) {
    const int i0 = 4 * wp;
    const uint32_t cnt = i0 == B_YF ? 4 : (i0 & ~8) == B_EMPTY ? 2 : 1;
#pragma unroll
    for (int i = 0; i < 4; i++) mbar_init(bars + 8 * (i0 + i), (i < 2 && i0 == B_YE) ? 128 : cnt);
    asm volatile("fence.mbarrier_init.release.cluster;" ::: "memory");
    if (i0 == B_SLAB) { mbar_expect(bars + 8 * B_PEER, 8192); mbar_expect(bars + 8 * (B_PEER + 1), 8192); }
  }
  __syncwarp();
  uint32_t kq[12];
  if (wp == 11) {
    if (elect()) { mbar_init(bars + 8 * B_X, 1); mbar_init(bars + 8 * B_RE, 1); mbar_init(bars + 8 * (B_A + 4), 1); asm volatile("fence.mbarrier_init.release.cluster;" ::: "memory"); mbar_expect(bars + 8 * B_X, 16 * 1152); }
    while ((uint32_t)clock() - tstart < DELAY2) __nanosleep(20);
    __syncwarp();
    nbar_arrive(1, 384);
    if (elect()) {
      while ((uint32_t)clock() - tstart < DELAY1) __nanosleep(20);
#pragma unroll 1
      for (int r = 0; r < 16; r++) bulk_load(sb + C_X + r * XP, P.q + (b * 16 + r) * D_, 1152, bars + 8 * B_X);
    }
    __syncwarp();
    TMW(53);
  } else {
    if (wp < 10) {
      if (wp < 8) { const uint32_t cval = wp < 4 ? 0u : ~0u; sts128(sb + M_CONST + tid * 16, cval, cval, cval, cval); }
      const uint32_t pl = sb + plane_of(wp >> 1) + (wp & 1) * CV_PL + lane * 16;
      sts128(pl, 0, 0, 0, 0); if (lane < 17 - (wp & 1)) sts128(pl + 512, 0, 0, 0, 0);
      PROXY_FENCE_SMEM();
    }
    uint32_t cv = 0, dv = 0;
    if (wp == 10) {
      asm volatile("ld.relaxed.gpu.global.u32 %0, [%1];" : "=r"(cv) : "l"(P.cnt + (lane < 16 ? min(lane, N_CNT - 1) * 32 : 1024 + min(lane & 7, 6) * 128 + b)) : "memory");
      asm volatile("ld.global.nc.u16 %0, [%1];" : "=r"(dv) : "l"(P.Dv + chan(min(lane & 7, 4))) : "memory");
    }
    if (EARLY0 && wp < 4) ssk_fetch(kq, P.ssk + chan(wg) * S_, tid & 127);
    nbar_sync(1, 384);
    if (wp == 10) {
      asm volatile("st.shared.b32 [%0], %1;" ::"r"(sb + M_SMALL + lane * 4), "r"(lane < 16 ? (cv & ~127u) + 128 : lane < 24 ? cv + 8 : dv << 16) : "memory"); TMW(52);
      nbar_arrive(2, 320);
      uint32_t bv[11];
#pragma unroll
      for (int i = 0; i < 11; i++) bv[i] = __ldg((const uint32_t*)(i < 9 ? P.b1 + j * 576 + 64 * i : i == 9 ? P.b2 + j * 64 : P.b2 + 512) + lane);
#pragma unroll
      for (int i = 0; i < 11; i++) { const float f = i < 9 ? 0.5f : 1.f;
        asm volatile("st.shared.v2.f32 [%0], {%1,%2};" ::"r"(sb + M_BIAS + i * 256 + lane * 8), "f"(f * blo(bv[i])), "f"(f * bhi(bv[i])) : "memory"); }
    }
    if (wp < 9) {
      {
        const int half = lane & 1, c0 = wp * 64 + (lane >> 1) * 4;
        uint32_t s0[4], s1[4];
        uint2 kr[11], vr[8];
        const uint32_t ka = sb + C_KV + half * KV_H + c0 * 2;
        if (wp < 8 && !(EARLY0 && wp < 4)) ssk_fetch(kq, P.ssk + chan(wg) * S_, tid & 127);
        if (wp >= 4) nbar_sync(2, 320);
        mbar_wait(bars + 8 * B_KV, 0);
        if (wg == 0) TM(50);
        lds128(s0[0], s0[1], s0[2], s0[3], sb + C_SK + c0 * 8); lds128(s1[0], s1[1], s1[2], s1[3], sb + C_SK + c0 * 8 + 16);
#pragma unroll
        for (int r = 0; r < 11; r++) asm volatile("ld.shared.v2.b32 {%0,%1}, [%2];" : "=r"(kr[r].x), "=r"(kr[r].y) : "r"(ka + r * 1152) : "memory");
#pragma unroll
        for (int r = 0; r < 8; r++) asm volatile("ld.shared.v2.b32 {%0,%1}, [%2];" : "=r"(vr[r].x), "=r"(vr[r].y) : "r"(ka + (11 + r) * 1152) : "memory");
        uint32_t wa[4], wb[4];
        wa[0] = __byte_perm(s0[0], s0[2], 0x5410); wa[1] = __byte_perm(s0[0], s0[2], 0x7632); wa[2] = __byte_perm(s0[1], s0[3], 0x5410); wa[3] = __byte_perm(s0[1], s0[3], 0x7632);
        wb[0] = __byte_perm(s1[0], s1[2], 0x5410); wb[1] = __byte_perm(s1[0], s1[2], 0x7632); wb[2] = __byte_perm(s1[1], s1[3], 0x5410); wb[3] = __byte_perm(s1[1], s1[3], 0x7632);
        if (b == 0 && half == 0) { kr[0] = kr[1] = kr[2] = make_uint2(0, 0); }
#pragma unroll
        for (int r = 0; r < 8; r++) {
          vr[r].x = bmul(bfma(kr[r + 3].x, wa[0], bfma(kr[r + 2].x, wa[1], bfma(kr[r + 1].x, wa[2], bmul(kr[r].x, wa[3])))), vr[r].x);
          vr[r].y = bmul(bfma(kr[r + 3].y, wb[0], bfma(kr[r + 2].y, wb[1], bfma(kr[r + 1].y, wb[2], bmul(kr[r].y, wb[3])))), vr[r].y);
        }
        uint4* dst = (uint4*)(P.kvT + c0 * S_ + 16 * b + 8 * half);
        const uint32_t stg = sb + C_KVO + (wp - 4) * 2048;
#pragma unroll
        for (int c = 0; c < 4; c++) {
          uint32_t o[4];
#pragma unroll
          for (int i = 0; i < 4; i++) o[i] = __byte_perm((c & 2) ? vr[2 * i].y : vr[2 * i].x, (c & 2) ? vr[2 * i + 1].y : vr[2 * i + 1].x, (c & 1) ? 0x7632 : 0x5410);
          if (wp < 4) { asm volatile("st.relaxed.gpu.global.v4.u32 [%0], {%1,%2,%3,%4};" ::"l"(dst + c * (S_ / 8)), "r"(o[0] ^ 0xffff0000u), "r"(o[1]), "r"(o[2]), "r"(o[3]) : "memory"); }
          else sts128(stg + c * 512 + lane * 16, o[0] ^ 0xffff0000u, o[1], o[2], o[3]);
        }
        if (wp < 4) { nbar_sync(2, 320); if (wp == 0 && elect()) hint_add(P.cnt + N_KVA * 32, 1); }
        TM(48 + (wg != 0));
      }
    }
    if (wp >= 4 && wp < 9 && wp != 7) nbar_arrive(7, 160);
    if (wp == 7) {
      nbar_sync(7, 160);
      if (elect()) {
        PROXY_FENCE_SMEM();
#pragma unroll 1
        for (int i = 4; i < 9; i++) asm volatile("cp.async.bulk.tensor.3d.global.shared::cta.bulk_group [%0, {%2, %3, %4}], [%1];" ::"l"(&P.tm_kv), "r"(sb + C_KVO + (i - 4) * 2048), "r"(16 * b), "r"(i * 16), "r"(0) : "memory");
        asm volatile("cp.async.bulk.commit_group;" ::: "memory"); asm volatile("cp.async.bulk.wait_group.read 0;" ::: "memory");
        hint_add(P.cnt + N_KVB * 32, 1);
      }
      __syncwarp();
      TMW(51);
    }
  }
  if (wg == 2) {
    asm volatile("setmaxnreg.dec.sync.aligned.u32 136;");
    {
    FRESH_IDS();
    const int pw = w;
    {
      const uint32_t xa = sb + C_X + (lane & 15) * XP + (w * 144 + (lane >> 4) * 8) * 2;
      const uint32_t xb = sb + C_X + (4 * ((lane & 7) >> 1) + (lane & 1) + ((lane >> 2) & 2)) * XP + (w * 144 + (lane >> 4) * 8) * 2;
      const uint32_t xo = sb + C_XO + w * 144 * 32, enc = (lane & 1) ? 0u : 0xffff0000u;
      float sa[4] = {0.f, 0.f, 0.f, 0.f}, g0[4] = {0.f, 0.f, 0.f, 0.f}, g1[4] = {0.f, 0.f, 0.f, 0.f}, g2[4] = {0.f, 0.f, 0.f, 0.f}, g3[4] = {0.f, 0.f, 0.f, 0.f};
      mbar_wait(bars + 8 * B_X, 0);
      TM(17);
      uint32_t p0, p1, f[36], t[36];
      asm volatile("ld.shared.u16 %0, [%1];" : "=r"(p0) : "r"(sb + C_X + g * XP) : "memory"); asm volatile("ld.shared.u16 %0, [%1];" : "=r"(p1) : "r"(sb + C_X + (g + 8) * XP) : "memory");
#pragma unroll
      for (int k = 0; k < 9; k++) ldsm4(f[4 * k], f[4 * k + 1], f[4 * k + 2], f[4 * k + 3], xa + k * 32);
#pragma unroll
      for (int k = 0; k < 9; k++) ldsm4t(t[4 * k], t[4 * k + 1], t[4 * k + 2], t[4 * k + 3], xb + k * 32);
      p0 *= 0x10001u; p1 *= 0x10001u;
#pragma unroll
      for (int k = 0; k < 9; k++) {
#pragma unroll
        for (int i = 0; i < 4; i++) asm("sub.rn.bf16x2 %0, %0, %1;" : "+r"(f[4 * k + i]) : "r"((i & 1) ? p1 : p0));
        mma16816(sa, &f[4 * k], 0x3f803f80u, 0x3f803f80u);
        mma1688(g0, f[4 * k], f[4 * k + 1], f[4 * k]); mma1688(g1, f[4 * k], f[4 * k + 1], f[4 * k + 1]);
        mma1688(g2, f[4 * k + 2], f[4 * k + 3], f[4 * k + 2]); mma1688(g3, f[4 * k + 2], f[4 * k + 3], f[4 * k + 3]);
        asm volatile("st.shared.v2.b32 [%0], {%1,%2};" ::"r"(xo + k * 512 + lane * 8), "r"(t[4 * k] ^ enc), "r"(t[4 * k + 1]) : "memory");
        asm volatile("st.shared.v2.b32 [%0], {%1,%2};" ::"r"(xo + k * 512 + 256 + lane * 8), "r"(t[4 * k + 2] ^ enc), "r"(t[4 * k + 3]) : "memory"); }
      if (t4 == (g >> 1)) asm volatile("st.shared.v4.f32 [%0], {%1,%2,%3,%4};" ::"r"(sb + M_STAT + g * 64 + w * 16), "f"(sa[0]), "f"(sa[2]),
                                       "f"((g & 1) ? g0[1] + g2[1] : g0[0] + g2[0]), "f"((g & 1) ? g1[3] + g3[3] : g1[2] + g3[2]) : "memory");
      nbar_arrive(13, 256);
      nbar_sync(5, 128);
      TM(5);
      if (w == 0) {
        uint32_t q[4]; lds128(q[0], q[1], q[2], q[3], sb + M_STAT + lane * 16);
        float e0 = __uint_as_float(q[0]), e1 = __uint_as_float(q[1]), v0 = __uint_as_float(q[2]), v1 = __uint_as_float(q[3]);
#pragma unroll
        for (int o = 1; o < 4; o <<= 1) { e0 += __shfl_xor_sync(~0u, e0, o); e1 += __shfl_xor_sync(~0u, e1, o); v0 += __shfl_xor_sync(~0u, v0, o); v1 += __shfl_xor_sync(~0u, v1, o); }
        e0 *= 1.f / D_; e1 *= 1.f / D_;
        const uint32_t rp = pack(rsqrtf(fmaxf(fmaf(-e0, e0, v0 * (1.f / D_)), 0.f) + 1e-5f), rsqrtf(fmaxf(fmaf(-e1, e1, v1 * (1.f / D_)), 0.f) + 1e-5f));
        const uint32_t np = pack(-(e0 + blo(p0)) * blo(rp), -(e1 + blo(p1)) * bhi(rp));
        const uint32_t mine = (t4 & 2) ? np : rp;
        uint32_t o[4];
#pragma unroll
        for (int i = 0; i < 4; i++) o[i] = __byte_perm(__shfl_sync(~0u, mine, 8 * i + t4), __shfl_sync(~0u, mine, 8 * i + 4 + t4), (t4 & 1) ? 0x7632 : 0x5410);
        if (lane < 4) asm volatile("st.relaxed.gpu.global.v4.u32 [%0], {%1,%2,%3,%4};" ::"l"(P.st1 + (lane >> 1) * 256 + 2 * b + (lane & 1)), "r"(o[0] ^ 0xffff0000u), "r"(o[1]), "r"(o[2]), "r"(o[3]) : "memory");
        nbar_arrive(0, 64);
      } else if (w == 1) {
        if (XLATE) nbar_sync(12, 160);
        if (lane == 0) { PROXY_FENCE_SMEM();
#pragma unroll 1
          for (int i = 0; i < 4; i++) tma2d_store(&P.tm_x, sb + C_XO + i * 144 * 32, 16 * b, i * 144);
          asm volatile("cp.async.bulk.commit_group;" ::: "memory"); asm volatile("cp.async.bulk.wait_group.read 0;" ::: "memory"); }
        __syncwarp();
        nbar_sync(0, 64);
        if (elect()) hint_add(P.cnt + N_X * 32, 1);
        __syncwarp();
        TMW(18);
      }
    }
    LOAD_SLICES();
    {
      const uint32_t yr = sb + C_Y + tl * 16;
      const uint4 *xp = (const uint4*)P.xT + b * 256 + tl, *xp4 = (const uint4*)P.xT + chan(4) * 256 + tl, *sp = P.st1 + tl;
      uint4 *hp = (uint4*)P.hT + (hrow + b) * 256 + tl, *hp4 = (uint4*)P.hT + (hrow + chan(4)) * 256 + tl;
      asm volatile("" : "+l"(xp), "+l"(xp4), "+l"(sp), "+l"(hp), "+l"(hp4));
      uint4 st[4], xv[10];
      uint32_t z[4][4];
      auto load_x = [&](auto ST, int part) {
#pragma unroll
        for (int i = 0; i < 4; i++) if (part == 0) st[i] = ld16<decltype(ST)::value>(sp + i * 128);
#pragma unroll
        for (int i = 0; i < 10; i++) if ((i >= 4) == part) xv[i] = ld16<decltype(ST)::value>((i < 8 ? xp + (i >> 1) * 128 * 256 : xp4) + (i & 1) * 128);
      };
      auto check_x = [&](int part) {
#pragma unroll 1
        for (int n = 0; n < 5000; n++) {
          uint32_t mn = part ? 0xffffffffu : min(min(st[0].x, st[1].x), min(st[2].x, st[3].x));
#pragma unroll
          for (int i = 0; i < 10; i++) if ((i >= 4) == part) mn = min(mn, xv[i].x);
          if (mn >= 0x10000u) break;
          load_x(IC<1>{}, part);
        }
        __syncwarp();
      };
      auto yf = [&](int u) { return bars + 8 * (B_YF + (u & 1) * 2 + ((u >> 1) & 1)); };
      auto sum = [&](int u) {
        const int hf = u & 1, g2 = (u >> 1) & 1;
        uint32_t y[16];
        mbar_wait(yf(u), (u >> 2) & 1);
#pragma unroll
        for (int ww = 0; ww < 4; ww++) lds128(y[4 * ww], y[4 * ww + 1], y[4 * ww + 2], y[4 * ww + 3], yr + g2 * CV_Y + hf * 2048 + ww * CV_YW);
#pragma unroll
        for (int r = 0; r < 4; r++) z[u & 3][r] = badd(badd(y[r], y[4 + r]), badd(y[8 + r], y[12 + r]));
        asm volatile("" : "+r"(z[u & 3][0]), "+r"(z[u & 3][1]), "+r"(z[u & 3][2]), "+r"(z[u & 3][3])::"memory");
        if (hf && u < 6) mbar_arrive(bars + 8 * (B_YE + g2));
      };
      auto gate = [&](int u, bool on) {
        const int hf = u & 1;
        const uint4 r = st[hf], n = st[2 + hf], x = xv[u];
        const uint32_t x0 = x.x ^ 0xffff0000u;
        const uint4 h = make_uint4(bfma(bfma(x0, r.x, n.x), z[u & 3][0], x0), bfma(bfma(x.y, r.y, n.y), z[u & 3][1], x.y), bfma(bfma(x.z, r.z, n.z), z[u & 3][2], x.z), bfma(bfma(x.w, r.w, n.w), z[u & 3][3], x.w));
        if (on) __stcg((u < 8 ? hp + (u >> 1) * 128 * 256 : hp4) + hf * 128, h);
      };
      auto publish = [&](int it) { const int id = it < 3 ? 9 + it : 15; if (pw) nbar_arrive(id, 128); else { nbar_sync(id, 128); if (elect()) hint_add(P.cnt + (N_H + it) * 32, 1); __syncwarp(); } };
      bool got = hint_try(P.cnt + N_X * 32, small_val(N_X), yf(1), 0);
      if (!got) { sum(0); sum(1); hint_wait(P.cnt + N_X * 32, small_val(N_X)); __syncwarp(); }
      load_x(IC<!WEAK>{}, 0);
      TM(7);
      if (got) { sum(0); sum(1); }
      sum(2); sum(3);
      check_x(0);
      load_x(IC<!WEAK>{}, 1);
#pragma unroll
      for (int i = 0; i < 4; i++) st[i].x ^= 0xffff0000u;
      TM(11);
      gate(0, true); gate(1, true); gate(2, true); gate(3, true); publish(1);
      if ((pw & 1) && elect()) {
        if (pw == 1) { if (W1PF) l2_prefetch(P.w1 + b * 20736, 41472); }
        else {
#pragma unroll 1
          for (int sg = 0; sg < 4; sg++) { mbar_expect(bars + 8 * (B_FULL + sg), ST_B); tma2d(sb + M_RING + sg * ST_B, &P.tm_w1, j * 576, sg * 144, bars + 8 * (B_FULL + sg)); } }
      }
      __syncwarp();
      TM(9);
      check_x(1);
      sum(4); gate(4, true); sum(5); gate(5, true); publish(2);
      TM(54);
      sum(6); gate(6, true); sum(7); gate(7, true); publish(3);
      TM(55);
      if (!odd) { sum(8); gate(8, true); }
      sum(9); gate(9, (tl >= 64) == odd);
      TM(10);
      nbar_sync(5, 128);
      if (pw == 0 && elect()) hint_add(P.cnt + (N_H + 4) * 32, 1);
      __syncwarp();
    }
    }
    asm volatile("setmaxnreg.dec.sync.aligned.u32 24;");
    FRESH_IDS();
    const int pw = w;
    LOAD_SLICES();
    auto fetch_late = [&](int it) {
      if (elect()) { hint_wait(P.cnt + (N_H + it) * 32, small_val(N_H + it)); asm volatile("fence.proxy.async.global;" ::: "memory"); load_slices(2 * it, it < 4 ? 2 * it + 2 : 9, bars + 8 * (B_A + it)); }
      __syncwarp();
      TMW(17 - it); };
    if (pw == 0) {
#pragma unroll 1
      for (int c = 1; c < 9; c++) {
#pragma unroll
        for (int sg = 0; sg < 4; sg++) {
          mbar_wait(bars + 8 * (B_EMPTY + sg), (c & 1) ^ 1);
          if (elect()) { mbar_expect(bars + 8 * (B_FULL + sg), ST_B); tma2d(sb + M_RING + sg * ST_B, &P.tm_w1, j * 576 + c * 64, sg * 144, bars + 8 * (B_FULL + sg)); }
          __syncwarp();
        }
      }
#pragma unroll 1
      for (int s = 0; s < 9; s++) {
        const uint32_t bb = bars + (s & 1) * 64, dst = sb + (s & 1) * M_PARK, ph = ((s >> 1) ^ s) & 1;
        const int col = (s == 0 ? 8 : (j ^ (8 - s))) * 64;
#pragma unroll
        for (int sg = 0; sg < 4; sg++) {
          mbar_wait(s == 1 ? bars + 8 * (B_EMPTY + (sg >> 1)) : bb + 8 * (B_EMPTY + sg), ph);
          if (elect()) { mbar_expect(bb + 8 * (B_FULL + sg), ST_B); tma2d(dst + sg * ST_B, &P.tm_w2, col, j * 576 + sg * 144, bb + 8 * (B_FULL + sg)); }
          __syncwarp();
        }
      }
    } else if (pw == 3) {
      fetch_late(4);
      if (elect()) {
        const uint16_t* pf = P.w2 + (j * 576 + m * 36) * D_;
#pragma unroll 1
        for (int p = 0; p < 9; p++) {
          mbar_wait_long(bars + 8 * (B_EMPTY + 1), p & 1);
          const int o = chan(p >> 1) * S_ + (p < 8 ? p & 1 : odd) * 1024;
          if (p < 8) l2_prefetch(pf + p * 2592, 5184);
          bulk_store(P.kvT + o, sb + M_CONST, 2048); bulk_store(P.xT + o, sb + M_CONST, 2048); bulk_store(P.hT + (D_ - hrow) * S_ + o, sb + M_CONST + 2048, 2048);
        }
        bulk_store(P.st1 + 2 * b, sb + M_CONST, 32); bulk_store(P.st1 + 256 + 2 * b, sb + M_CONST, 32);
        asm volatile("cp.async.bulk.commit_group;" ::: "memory"); asm volatile("cp.async.bulk.wait_group.read 0;" ::: "memory");
        mbar_wait(bars + 8 * (B_EMPTY + 3), 0); mbar_wait_long(bars + 8 * (B_EMPTY + 2), 1); mbar_wait(bars + 8 * (B_EMPTY + 3), 1);
        mbar_arrive(bars + 8 * B_STEP);
      }
      __syncwarp();
#pragma unroll 1
      for (int t = 0; t < 7; t++) {
        unsigned* hp = P.cnt + 1024 + t * 128 + (t == 0 ? (b & ~7) + (lane & 7) : b ^ (8 - t));
        if (t) { mbar_wait_long(bars + (t & 1) * 64 + 8 * B_EMPTY, ((t >> 1) ^ t ^ 1) & 1); mbar_wait(bars + (t & 1) * 64 + 8 * (B_EMPTY + 3), ((t >> 1) ^ t ^ 1) & 1); }
        if (lane < (t == 0 ? 8 : 1)) hint_add(hp, t == 0 ? 1 : 8);
        __syncwarp();
      }
    } else if (pw == 2) {
      fetch_late(3);
      mbar_wait_long(bars + 8 * B_STEP, 0);
#pragma unroll 1
      for (int s = 0; s < 7; s++) {
        if (lane == s) { hint_wait(P.cnt + 1024 + s * 128 + b, small_val(16 + s)); mbar_arrive(bars + 8 * (B_HINT + s)); }
        __syncwarp();
      }
    } else {
      if (elect()) { grid_arrive(P.cnt + N_F * 32); mbar_wait(bars + 8 * (B_EMPTY + 3), 0); grid_wait(P.cnt + N_F * 32, small_val(N_F)); }
      __syncwarp();
      mbar_wait_long(bars + 8 * B_STEP, 0);
      if (elect()) {
        asm volatile("fence.proxy.async.global;" ::: "memory");
        mbar_expect(bars + 8 * B_H, 2 * 16384);
        tma3d(sb + M_PARK + 7 * 16384, &P.tm_h2, 0, hrow + j * 64, 2 * m, bars + 8 * B_H);
        tma3d(sb + M_PARK + 5 * 16384, &P.tm_h2, 0, hrow + 512, 2 * m, bars + 8 * B_H);
        asm volatile("mbarrier.arrive.release.cluster.shared::cluster.b64 _, [%0];" ::"r"((bars ^ PEER) + 8 * B_RDY) : "memory");
      }
      __syncwarp();
      mbar_wait(bars + 8 * B_HINT, 0);
      const uint32_t pa = sb + M_PARK + 8 * 16384 + lane * 16, tag = (small_val(N_F) >> 7) & 1;
      const uint32_t hl = sb + M_PARK + (10 + (j >> 2)) * 8192 + ((lane >> 4) * 8 + (lane & 7)) * 128 + (((((lane >> 3) & 1) + 2 * (j & 3)) ^ (lane & 7)) * 16);
      mbar_wait(bars + 8 * B_H, 0);
#pragma unroll 1
      for (int it = 0; it < 2000; it++) {
        if (elect()) { mbar_expect(bars + 8 * B_SLAB, 16384); bulk_load(sb + M_PARK + 8 * 16384, P.part + (b << (DSH - 4)), 16384, bars + 8 * B_SLAB); }
        __syncwarp();
        mbar_wait(bars + 8 * B_SLAB, it & 1);
        uint32_t bad = 0;
#pragma unroll 1
        for (int i = 0; i < 4; i++) {
          float sm[8];
          uint32_t u[4];
          ldsm4t(u[0], u[1], u[2], u[3], hl + i * 2048);
          asm volatile("ld.shared.v2.f32 {%0,%1}, [%2];" : "=f"(sm[0]), "=f"(sm[1]) : "r"(sb + M_B2 + 256 + t4 * 8 + i * 64) : "memory");
          asm volatile("ld.shared.v2.f32 {%0,%1}, [%2];" : "=f"(sm[4]), "=f"(sm[5]) : "r"(sb + M_B2 + 256 + t4 * 8 + i * 64 + 32) : "memory");
          sm[2] = sm[0]; sm[3] = sm[1]; sm[6] = sm[4]; sm[7] = sm[5];
#pragma unroll 1
          for (int src = 0;; src++) {
#pragma unroll
            for (int r = 0; r < 4; r++) { sm[2 * r] += blo(u[r]); sm[2 * r + 1] += bhi(u[r]); }
            if (src == 8) break;
            lds128(u[0], u[1], u[2], u[3], pa + i * 512 + src * 2048);
            u[0] ^= tag; bad |= u[0];
          }
          uint16_t* op = P.out + (m * 128 + j * 16 + g) * D_ + 512 + 2 * t4 + i * 16;
#pragma unroll
          for (int r = 0; r < 4; r++) *(uint32_t*)(op + (r & 1) * 8 * D_ + (r >> 1) * 8) = pack(sm[2 * r], sm[2 * r + 1]);
        }
        if (!__any_sync(~0u, bad & 1)) break;
      }
    }
  } else {
    {
      FRESH_IDS();
      uint32_t a0[64];
      TM(57);
      const uint32_t pofs = sb + (8 + 16 * w + g + 8 - 2 * t4) * 4;
      const uint32_t ya = sb + C_Y + wg * CV_Y + w * (CV_YW + 32) + lane * 16;
      const uint32_t bfull = bars + 8 * (B_YF + wg);
      uint32_t u[8];
      {
        build_pairs(kq, sb + pairs_of(wg), tl, __uint_as_float(small_val(24 + wg)));
        uint32_t kn[3][12];
        const uint16_t *sr = P.ssk + (b + 256) * S_, *sr4 = P.ssk + chan(4) * S_;
        asm volatile("" : "+l"(sr), "+l"(sr4));
        if (wg && !SLATE) { ssk_fetch(kn[0], sr, tl); ssk_fetch(kn[1], sr + 128 * S_, tl); ssk_fetch(kn[2], sr4, tl); }
        nbar_sync(3 + wg, 128);
        conv_lda<0, 16>(a0, pofs + pairs_of(wg));
        asm volatile("setmaxnreg.inc.sync.aligned.u32 184;");
        TM(16);
        if (wp == 0) hint_wait(P.cnt + N_KVA * 32, small_val(N_KVA));
        if (wg) nbar_sync(6, 256); else { nbar_arrive(6, 256); nbar_sync(3, 128); }
        TM(3 + wg);
        kv_fetch(u, P.kvT + chan(wg) * S_ + tl * 8);
        if (XLATE == 3 && wg == 0) nbar_arrive(12, 160);
        if (wg && SLATE) { ssk_fetch(kn[0], sr, tl); ssk_fetch(kn[1], sr + 128 * S_, tl); ssk_fetch(kn[2], sr4, tl); }
        if (lane < 2 * w) sts128(ya - 32 * w, 0, 0, 0, 0);
        if (wg) {
          if (w == 0) { hint_wait(P.cnt + N_KVB * 32, small_val(N_KVB)); __syncwarp(); if (elect()) mbar_arrive(bars + 8 * B_PL); __syncwarp(); }
#pragma unroll
          for (int i = 0; i < 3; i++) build_pairs(kn[i], sb + pairs_of(2 + i), tl, __uint_as_float(small_val(26 + i)));
          nbar_arrive(1, 256);
          TM(56);
        }
      }
#pragma unroll 1
      for (int it = wg; it < 5; it += 2) {
        kv_place(u, P.kvT + chan(it) * S_ + tl * 8, sb + plane_of(it) + 768 + tl * 16);
        if (XLATE == 1 && it == 0) nbar_arrive(12, 160);
        PROXY_FENCE_SMEM();
        const uint64_t db = mkdesc(SB + plane_of(it) + 768, CV_PL, 128, 0);
        mbar_wait(bfull + 32, ((it >> 1) & 1) ^ 1);
        nbar_sync(13 + wg, 256);
        if (it < 2) TM(19 + wg * 16);
        float c0 = 0.f, c1 = 0.f;
        if (EARLYH && it == 3) asm volatile("ld.relaxed.gpu.global.u32 %0, [%1];" : "=r"(u[0]) : "l"(P.cnt + (N_H + 1) * 32) : "memory");
        if (it == 4 && odd) {
          float d[32], e[32];
          WG_FENCE(); conv_mma<2>(d, a0, db); conv_mma<3>(e, a0, db); WG_COMMIT();
          WG_WAIT0(); pin(d); pin(e);
          conv_out<2>(d, c0, c1, ya); conv_out<3>(e, c0, c1, ya);
        } else {
          float d[32], e[32];
          WG_FENCE(); conv_mma<0>(d, a0, db); WG_COMMIT(); conv_mma<1>(e, a0, db); WG_COMMIT();
          WG_WAIT1(); pin(d);
          conv_out<0>(d, c0, c1, ya);
          WG_FENCE(); conv_mma<2>(d, a0, db); WG_COMMIT();
          if (HO == 1 && it < 4) nbar_arrive(13 + (wg ^ 1), 256);
          WG_WAIT1(); pin(e);
          conv_out<1>(e, c0, c1, ya);
          __syncwarp();
          if (lane == 0) mbar_arrive(bfull);
          if (it == 4) { WG_WAIT0(); pin(d); conv_out<2>(d, c0, c1, ya); }
          else {
            if (HO == 2) nbar_arrive(13 + (wg ^ 1), 256);
            WG_FENCE(); conv_mma<3>(e, a0, db); WG_COMMIT();
            if (HO == 3) nbar_arrive(13 + (wg ^ 1), 256);
            if (it < 3) { mbar_wait(bars + 8 * B_PL, 0); kv_fetch(u, P.kvT + chan(it + 2) * S_ + tl * 8); }
            WG_WAIT0(); pin(d); pin(e);
            conv_out<2>(d, c0, c1, ya); conv_out<3>(e, c0, c1, ya);
          }
        }
        __syncwarp();
        if (lane == 0) mbar_arrive(bfull + 16);
        if (it == 0) nbar_sync(1, 256);
        if (it < 3) conv_lda<0, 16>(a0, pofs + pairs_of(it + 2));
        if (it == 2) nbar_arrive(2, 256);
        TM(20 + (it >> 1) + wg * 16);
      }
      if (wg) {
        LOAD_SLICES();
        if (w == 1 && !(EARLYH && (int)(u[0] - small_val(N_H + 1)) >= 0)) hint_wait(P.cnt + (N_H + 1) * 32, small_val(N_H + 1));
        nbar_sync(2, 256);
        TM(12);
        if (w == 0 && elect()) { asm volatile("fence.proxy.async.global;" ::: "memory"); load_slices(0, 2, bars + 8 * B_A); load_slices(2, 4, bars + 8 * (B_A + 1));
          hint_wait(P.cnt + (N_H + 2) * 32, small_val(N_H + 2)); asm volatile("fence.proxy.async.global;" ::: "memory"); load_slices(4, 6, bars + 8 * (B_A + 2)); }
        __syncwarp();
        TM(15);
      }
    }
    asm volatile("setmaxnreg.inc.sync.aligned.u32 240;");
    FRESH_IDS();
    const bool leader = tl == 0;
    const uint32_t reg = sb + M_PARK + wg * 8192;
    const uint32_t lma = (((lane >> 4) * 8 + (lane & 7)) * 128) + (((((lane >> 3) & 1) + 2 * w) ^ (lane & 7)) * 16);
    uint32_t a[144];
    float r0, r1, m0, m1;
#pragma unroll 1
    for (int pass = 0;; pass++) {
      float sa[4] = {0.f, 0.f, 0.f, 0.f}, g0[4] = {0.f, 0.f, 0.f, 0.f}, g1[4] = {0.f, 0.f, 0.f, 0.f}, g2[4] = {0.f, 0.f, 0.f, 0.f}, g3[4] = {0.f, 0.f, 0.f, 0.f};
      auto group = [&](auto GR, auto K0, auto K1) {
        constexpr int gr = decltype(GR)::value, k0 = decltype(K0)::value, k1 = decltype(K1)::value;
        mbar_wait(bars + 8 * (B_A + gr), 0);
        if (gr == 0 || gr == 4) TM(gr ? 23 + wg * 16 : 58 + wg);
#pragma unroll
        for (int k = k0; k < k1; k++) ldsm4t(a[4 * k], a[4 * k + 1], a[4 * k + 2], a[4 * k + 3], reg + lma + (k >> 2) * 16384 + (k & 3) * 2048);
#pragma unroll
        for (int k = k0; k < k1; k++) { mma16816(sa, &a[4 * k], 0x3f803f80u, 0x3f803f80u);
          mma1688(g0, a[4 * k], a[4 * k + 1], a[4 * k]); mma1688(g1, a[4 * k], a[4 * k + 1], a[4 * k + 1]);
          mma1688(g2, a[4 * k + 2], a[4 * k + 3], a[4 * k + 2]); mma1688(g3, a[4 * k + 2], a[4 * k + 3], a[4 * k + 3]); }
        asm volatile("" : "+f"(sa[0]), "+f"(g0[0]), "+f"(g1[0]), "+f"(g2[0]), "+f"(g3[0])::"memory");
      };
      group(IC<0>{}, IC<0>{}, IC<8>{}); group(IC<1>{}, IC<8>{}, IC<16>{}); group(IC<2>{}, IC<16>{}, IC<24>{}); group(IC<3>{}, IC<24>{}, IC<32>{}); group(IC<4>{}, IC<32>{}, IC<36>{});
      m0 = sa[0] * (1.f / D_); m1 = sa[2] * (1.f / D_);
      r0 = (g & 1) ? g0[1] + g2[1] : g0[0] + g2[0]; r1 = (g & 1) ? g1[3] + g3[3] : g1[2] + g3[2];
      uint32_t bad;
      asm volatile("{.reg .pred p, q; .reg .f32 t; add.f32 t, %1, %2; add.f32 t, t, %3; add.f32 t, t, %4; setp.nan.f32 p, t, t; bar.red.or.pred q, 6, 256, p; selp.u32 %0, 1, 0, q;}"
                   : "=r"(bad) : "f"(m0), "f"(m1), "f"(r0), "f"(r1) : "memory");
      const uint32_t tf = small_val(N_F);
      if ((!bad && tf != 128) || pass) break;
      if (tid == 0) { grid_wait(P.cnt + N_F * 32, tf); PROXY_FENCE_SMEM(); mbar_expect(bars + 8 * B_RE, 9 * 16384);
#pragma unroll 1
        for (int s = 0; s < 9; s++) tma3d(sb + M_PARK + s * 16384, &P.tm_h2, 0, ((tf >> 7) & 1) * D_ + s * 64, 2 * m, bars + 8 * B_RE); }
      __syncwarp();
      mbar_wait(bars + 8 * B_RE, 0);
    }
    float d0[32], d1[32];
    uint32_t park = reg + tl * 16, ba = sb + M_BIAS + t4 * 8;
    float bv[4];
    {
      const uint32_t n0 = pack(m0, m0), n1 = pack(m1, m1);
      center<0>(a, n0, n1);
      mbar_wait(bars + 8 * B_FULL, 0);
      TM(24 + wg * 16); TC(0);
#pragma unroll
      for (int sg = 0; sg < 4; sg++) {
        mma_stage(d0, a, sg);
        mbar_wait(bars + 8 * (B_FULL + ((sg + 1) & 3)), sg == 3);
        if (sg == 0) center<36>(a, n0, n1);
        if (sg == 1) center<72>(a, n0, n1);
        if (sg == 2) center<108>(a, n0, n1);
        if (sg == 3) { const int src = (lane & ~3) | (g >> 1);
          r0 = 0.5f * rsqrtf(fmaxf(fmaf(-m0, m0, __shfl_sync(~0u, r0, src) * (1.f / D_)), 0.f) + 1e-5f);
          r1 = 0.5f * rsqrtf(fmaxf(fmaf(-m1, m1, __shfl_sync(~0u, r1, src) * (1.f / D_)), 0.f) + 1e-5f);
          ld_bias(bv, ba); asm volatile("" : "+f"(r0), "+f"(r1)::"memory"); mbar_wait(bars + 8 * B_KV, 0); }
        WG_WAIT0();
        if (leader) mbar_arrive(bars + 8 * (B_EMPTY + sg));
      }
      pin(d0);
      TC(1);
    }
#pragma unroll 1
    for (int c = 0; c < 4; c++) {
      chunk1<false>(false, d1, d0, a, bars, 1, park, ba, leader, r0, r1, bv);
      TC(2 + 2 * c);
      chunk1<true>(c == 3, d0, d1, a, bars, 0, park + 16384, ba + 256, leader, r0, r1, bv);
      TC(3 + 2 * c);
      park += 32768; ba += 512;
    }
    TM(25 + wg * 16); TC(10);
    park -= 8 * 16384;
    uint32_t tag, io;
    auto send = [&](const char* outp) {
#pragma unroll
      for (int i = 0; i < 4; i++)
        asm volatile("st.relaxed.gpu.global.v4.u32 [%0], {%1,%2,%3,%4};" ::"l"(outp + i * 512), "r"((pack(d1[8 * i], d1[8 * i + 1]) & ~1u) | tag), "r"(pack(d1[8 * i + 2], d1[8 * i + 3])),
                     "r"(pack(d1[8 * i + 4], d1[8 * i + 5])), "r"(pack(d1[8 * i + 6], d1[8 * i + 7])) : "memory");
    };
    {
      const char* outp;
#pragma unroll
      for (int sg = 0; sg < 4; sg++) {
        mma_stage(d1, a, sg);
        mbar_wait(bars + 8 * (sg < 3 ? B_FULL + sg + 1 : B_FULL + 8), sg < 3);
        if (sg == 0) gelu_last<0, 3, 18, 23>(d0, r0, r1, ba, a, park);
        if (sg == 1) gelu_last<3, 6, 23, 27>(d0, r0, r1, ba, a, park);
        if (sg == 2) gelu_last<6, 8, 27, 32>(d0, r0, r1, ba, a, park);
        if (sg == 3) {
#pragma unroll
          for (int n = 0; n < 16; n++) asm volatile("ld.shared.v2.f32 {%0,%1}, [%2];" : "=f"(d0[2 * n]), "=f"(d0[2 * n + 1]) : "r"(sb + M_B2 + t4 * 8 + (n >> 1) * 32) : "memory");
          tag = ((small_val(N_F) >> 7) & 1) ^ (tid >> 10); io = (b << DSH) | ((tid & 31) << 4) | ((tid >> 5) << 11);
          outp = (const char*)P.part + (((b & ~7) << DSH) | ((tid >> 5) << DSH) | (j << 11) | ((tid & 31) << 4));
          asm volatile("" : "+l"(outp), "+r"(tag), "+r"(io));
        }
        mbar_wait(bars + 8 * (sg < 3 ? B_KV : B_FULL + 9), 0);
        WG_WAIT0();
        if (leader && sg < 3) mbar_arrive(bars + 8 * (B_EMPTY + sg));
      }
      pin(d1);
      TC(11);
      send(outp);
      if (leader) mbar_arrive(bars + 8 * (B_EMPTY + 3));
    }
    uint32_t pi[16];
#pragma unroll
    for (int i = 0; i < 16; i++) asm volatile("" : "=r"(pi[i]));
#pragma unroll 1
    for (int s = 1;; s++) {
      const uint32_t ph = ((s >> 1) ^ s ^ 1) & 1, bb = bars + (s & 1) * 64, buf16 = (s & 1) * (M_PARK / 16);
      const char* outp = nullptr;
      auto add_peer = [&](int i) { uint32_t u[4]; lds128(u[0], u[1], u[2], u[3], park + 6 * 16384 + i * 2048);
#pragma unroll
        for (int r = 0; r < 4; r++) { d0[8 * i + 2 * r] += blo(u[r]); d0[8 * i + 2 * r + 1] += bhi(u[r]); asm volatile("" : "+f"(d0[8 * i + 2 * r]), "+f"(d0[8 * i + 2 * r + 1])::"memory"); } };
      mma_half(d1, a, 0, buf16);
      if (s >= 3) { add_part<NB_, 16>(d0, pi); mbar_wait(bars + 8 * (B_HINT + s - 2), 0); ld_part(pi, (const char*)P.part + (io + ((s - 2) << SSH)));
        if (s == 8) { mbar_wait(bars + 8 * (B_PEER + wg), 0); add_peer(0); add_peer(1); } }
      else if (s == 2) { mbar_wait(bars + 8 * B_H, 0);
#pragma unroll
        for (int i = 0; i < 4; i++) ldsm4t(pi[4 * i], pi[4 * i + 1], pi[4 * i + 2], pi[4 * i + 3], reg + 7 * 16384 + lma + i * 2048);
      }
      mbar_wait(bb + 8 * (B_FULL + 2), ph); mbar_wait(bb + 8 * (B_FULL + 3), ph);
      WG_WAIT0();
      if (tl < 2) mbar_arrive(bb + 8 * (B_EMPTY + tl));
      mma_half(d1, a, 1, buf16);
      if (s == 8) { add_peer(2); add_peer(3); }
      if (s >= 2) { if (s >= 3) poll_part(pi, P.part, io, s - 2, tag); add_part<0, NB_>(d0, pi); }
      if (s == 8) add_part<NB_, 16>(d0, pi);
      else { outp = (const char*)P.part + (io ^ ((s << SSH) | ((8 - s) << DSH))); asm volatile("" : "+l"(outp));
        const uint32_t nb = bars + 64 - (s & 1) * 64 + 8 * B_FULL; mbar_wait(nb, (s >> 1) & 1); mbar_wait(nb + 8, (s >> 1) & 1); }
      WG_WAIT0();
      pin(d1);
      TC(11 + s);
      if (s == 8) break;
      if (s < 7) send(outp);
      else {
        mbar_wait(bars + 8 * B_RDY, 0);
#pragma unroll
        for (int i = 0; i < 4; i++)
          asm volatile("st.async.weak.shared::cluster.mbarrier::complete_tx::bytes.v4.b32 [%0], {%1,%2,%3,%4}, [%5];" ::"r"((park ^ PEER) + 6 * 16384 + i * 2048),
                       "r"(pack(d1[8 * i], d1[8 * i + 1])), "r"(pack(d1[8 * i + 2], d1[8 * i + 3])), "r"(pack(d1[8 * i + 4], d1[8 * i + 5])), "r"(pack(d1[8 * i + 6], d1[8 * i + 7])),
                       "r"((bars ^ PEER) + 8 * (B_PEER + wg)) : "memory");
        TM(27 + wg * 16);
      }
      if (tl < 2) mbar_arrive(bb + 8 * (B_EMPTY + 2 + tl));
    }
    TM(28 + wg * 16);
    const uint32_t ob = reg + 7 * 16384 + w * 2048;
    const int orow = lane & 15;
#pragma unroll
    for (int i = 0; i < 4; i++) {
      uint32_t o[4];
#pragma unroll
      for (int r = 0; r < 4; r++) o[r] = pack(d0[8 * i + 2 * r] + d1[8 * i + 2 * r], d0[8 * i + 2 * r + 1] + d1[8 * i + 2 * r + 1]);
      stsm4(ob + orow * 128 + (((2 * i + (lane >> 4)) ^ (orow & 7)) * 16), o[0], o[1], o[2], o[3]);
    }
    PROXY_FENCE_SMEM();
    __syncwarp();
    if (elect()) { tma2d_store(&P.tm_o, ob, j * 64, m * 128 + wg * 64 + w * 16); asm volatile("cp.async.bulk.commit_group;" ::: "memory"); asm volatile("cp.async.bulk.wait_group.read 0;" ::: "memory"); }
    __syncwarp();
    TM(29 + wg * 16);
    TMFLUSH();
  }
}

typedef CUresult (*EncFn)(CUtensorMap*, CUtensorMapDataType, cuuint32_t, void*, const cuuint64_t*, const cuuint64_t*, const cuuint32_t*, const cuuint32_t*,
                          CUtensorMapInterleave, CUtensorMapSwizzle, CUtensorMapL2promotion, CUtensorMapFloatOOBfill);
void mk2d(EncFn enc, CUtensorMap* m, void* p, uint64_t inner, uint64_t outer, uint32_t bi, uint32_t bo, CUtensorMapSwizzle sw = CU_TENSOR_MAP_SWIZZLE_128B) {
  cuuint64_t d[2] = {inner, outer}, s[1] = {inner * 2}; cuuint32_t b[2] = {bi, bo}, e[2] = {1, 1};
  enc(m, CU_TENSOR_MAP_DATA_TYPE_BFLOAT16, 2, p, d, s, b, e, CU_TENSOR_MAP_INTERLEAVE_NONE, sw, CU_TENSOR_MAP_L2_PROMOTION_L2_128B, CU_TENSOR_MAP_FLOAT_OOB_FILL_NONE);
}
}

extern "C" void kernel_launch(void* const* d_in, const int* in_sizes, int n_in, void* d_out, int out_size) {
  void* f = nullptr; cudaDriverEntryPointQueryResult qr;
  cudaGetDriverEntryPoint("cuTensorMapEncodeTiled", &f, cudaEnableDefault, &qr);
  EncFn enc = (EncFn)f;
  void* hT; cudaGetSymbolAddress(&hT, g_hT);
  Params P;
  mk2d(enc, &P.tm_w1, d_in[7], F_, D_, 64, 144); mk2d(enc, &P.tm_w2, d_in[9], D_, F_, 64, 144); mk2d(enc, &P.tm_o, d_out, D_, S_, 64, 16);
  P.q = (const uint16_t*)d_in[0]; P.k = (const uint16_t*)d_in[1]; P.v = (const uint16_t*)d_in[2]; P.sk = (const uint16_t*)d_in[3]; P.ssk = (const uint16_t*)d_in[4];
  P.Dv = (const uint16_t*)d_in[5]; P.w1 = (const uint16_t*)d_in[7]; P.b1 = (const uint16_t*)d_in[8]; P.w2 = (const uint16_t*)d_in[9]; P.b2 = (const uint16_t*)d_in[10];
  P.out = (uint16_t*)d_out; P.hT = (uint16_t*)hT;
  cudaGetSymbolAddress((void**)&P.kvT, g_kvT); cudaGetSymbolAddress((void**)&P.xT, g_xT); cudaGetSymbolAddress((void**)&P.st1, g_st1);
  cudaGetSymbolAddress((void**)&P.part, g_part); cudaGetSymbolAddress((void**)&P.cnt, g_cnt); P.tm = nullptr;
  mk2d(enc, &P.tm_x, P.xT, S_, D_, 16, 144, CU_TENSOR_MAP_SWIZZLE_NONE);
  { cuuint64_t d[3] = {S_, D_ / 4, 4}, st[2] = {4 * S_ * 2, S_ * 2}; cuuint32_t bx[3] = {16, 16, 4}, e[3] = {1, 1, 1};
    enc(&P.tm_kv, CU_TENSOR_MAP_DATA_TYPE_BFLOAT16, 3, P.kvT, d, st, bx, e, CU_TENSOR_MAP_INTERLEAVE_NONE, CU_TENSOR_MAP_SWIZZLE_NONE, CU_TENSOR_MAP_L2_PROMOTION_NONE, CU_TENSOR_MAP_FLOAT_OOB_FILL_NONE); }
  { cuuint64_t d[3] = {64, 2 * D_, S_ / 64}, st[2] = {S_ * 2, 128}; cuuint32_t bx[3] = {64, 64, 2}, e[3] = {1, 1, 1};
    enc(&P.tm_h2, CU_TENSOR_MAP_DATA_TYPE_BFLOAT16, 3, P.hT, d, st, bx, e, CU_TENSOR_MAP_INTERLEAVE_NONE, CU_TENSOR_MAP_SWIZZLE_128B, CU_TENSOR_MAP_L2_PROMOTION_L2_128B, CU_TENSOR_MAP_FLOAT_OOB_FILL_NONE); }
  cudaFuncSetAttribute(k_fused, cudaFuncAttributeMaxDynamicSharedMemorySize, M_SMEM);
  k_fused<<<128, 384, M_SMEM>>>(P);
}
```

```cpp
#include <cuda_runtime.h>
#include <cuda.h>
#include <cuda_bf16.h>
#include <stdint.h>

namespace {
constexpr int S_ = 2048, D_ = 576, F_ = 4608;

__device__ __forceinline__ uint32_t s2u(const void* p) { return (uint32_t)__cvta_generic_to_shared(p); }
__device__ __forceinline__ uint64_t mkdesc(uint32_t addr, uint32_t lbo, uint32_t sbo, int sw) {
  return (uint64_t)((addr & 0x3FFFF) >> 4) | ((uint64_t)(lbo >> 4) << 16) | ((uint64_t)(sbo >> 4) << 32) | ((uint64_t)sw << 62);
}
__device__ __forceinline__ void mbar_init(uint32_t b, int c) { asm volatile("mbarrier.init.shared::cta.b64 [%0], %1;" ::"r"(b), "r"(c)); }
__device__ __forceinline__ void mbar_expect(uint32_t b, uint32_t tx) { asm volatile("mbarrier.arrive.expect_tx.shared::cta.b64 _, [%0], %1;" ::"r"(b), "r"(tx) : "memory"); }
__device__ __forceinline__ void mbar_arrive(uint32_t b) { asm volatile("mbarrier.arrive.shared::cta.b64 _, [%0];" ::"r"(b) : "memory"); }
__device__ __forceinline__ void mbar_wait(uint32_t b, uint32_t ph) {
  asm volatile("{\n.reg .pred p;\n.reg .u32 n;\nmov.u32 n, 0;\nLW:\nmbarrier.try_wait.parity.shared::cta.b64 p, [%0], %1;\n@p bra LD;\n"
               "add.u32 n, n, 1;\nsetp.lt.u32 p, n, 20000;\n@p bra LW;\nLD:\n}" ::"r"(b), "r"(ph) : "memory");
}
__device__ __forceinline__ void mbar_wait_hot(uint32_t b, uint32_t ph) {
  asm volatile("{\n.reg .pred p;\n.reg .u32 n;\nmbarrier.try_wait.parity.shared::cta.b64 p, [%0], %1;\n@p bra LD;\nmov.u32 n, %%clock;\nand.b32 n, n, 7;\n"
               "LW:\nmbarrier.try_wait.parity.shared::cta.b64 p, [%0], %1;\n@p bra LD;\n"
               "add.u32 n, n, 1;\nsetp.lt.u32 p, n, 20000;\n@p bra LW;\nLD:\n}" ::"r"(b), "r"(ph) : "memory");
}
__device__ __forceinline__ void mbar_wait_long(uint32_t b, uint32_t ph) {
  asm volatile("{\n.reg .pred p;\n.reg .u32 n;\nmov.u32 n, 0;\nLW:\nmbarrier.test_wait.parity.shared::cta.b64 p, [%0], %1;\n@p bra LD;\nnanosleep.u32 200;\n"
               "add.u32 n, n, 1;\nsetp.lt.u32 p, n, 10000;\n@p bra LW;\nLD:\n}" ::"r"(b), "r"(ph) : "memory");
}
__device__ __forceinline__ void sched_fence(uint32_t b) {
  asm volatile("{\n.reg .pred p;\nmbarrier.test_wait.parity.shared::cta.b64 p, [%0], 0;\n@p bra LD;\nnanosleep.u32 0;\nLD:\n}" ::"r"(b) : "memory");
}
__device__ __forceinline__ void flag_wait(const unsigned* p, unsigned target) {
  asm volatile("{\n.reg .pred p;\n.reg .u32 n, v;\nmov.u32 n, 0;\nLW:\nld.acquire.gpu.global.u32 v, [%0];\nsetp.ge.u32 p, v, %1;\n@p bra LD;\n"
               "add.u32 n, n, 1;\nsetp.lt.u32 p, n, 2000000;\n@p bra LW;\nLD:\n}" ::"l"(p), "r"(target) : "memory");
}
__device__ __forceinline__ void tma2d(uint32_t dst, const CUtensorMap* m, int c0, int c1, uint32_t bar) {
  asm volatile("cp.async.bulk.tensor.2d.shared::cluster.global.mbarrier::complete_tx::bytes [%0], [%1, {%3, %4}], [%2];" ::"r"(dst), "l"(m), "r"(bar), "r"(c0), "r"(c1) : "memory");
}
__device__ __forceinline__ void tma2d_store(const CUtensorMap* m, uint32_t src, int c0, int c1) {
  asm volatile("cp.async.bulk.tensor.2d.global.shared::cta.bulk_group [%0, {%2, %3}], [%1];" ::"l"(m), "r"(src), "r"(c0), "r"(c1) : "memory");
}
__device__ __forceinline__ void bulk_load(uint32_t dst, const void* src, uint32_t bytes, uint32_t bar) {
  asm volatile("cp.async.bulk.shared::cluster.global.mbarrier::complete_tx::bytes [%0], [%1], %2, [%3];" ::"r"(dst), "l"(src), "r"(bytes), "r"(bar) : "memory");
}
__device__ __forceinline__ void bulk_store(void* dst, uint32_t src, uint32_t bytes) {
  asm volatile("cp.async.bulk.global.shared::cta.bulk_group [%0], [%1], %2;" ::"l"(dst), "r"(src), "r"(bytes) : "memory");
}
__device__ __forceinline__ void l2_prefetch(const void* p, uint32_t bytes) { asm volatile("cp.async.bulk.prefetch.L2.global [%0], %1;" ::"l"(p), "r"(bytes) : "memory"); }
__device__ __forceinline__ void mma16816(float (&d)[4], const uint32_t* a, uint32_t b0, uint32_t b1) {
  asm("mma.sync.aligned.m16n8k16.row.col.f32.bf16.bf16.f32 {%0,%1,%2,%3}, {%4,%5,%6,%7}, {%8,%9}, {%0,%1,%2,%3};"
      : "+f"(d[0]), "+f"(d[1]), "+f"(d[2]), "+f"(d[3]) : "r"(a[0]), "r"(a[1]), "r"(a[2]), "r"(a[3]), "r"(b0), "r"(b1));
}
__device__ __forceinline__ void mma1688(float (&d)[4], uint32_t a0, uint32_t a1, uint32_t b0) {
  asm("mma.sync.aligned.m16n8k8.row.col.f32.bf16.bf16.f32 {%0,%1,%2,%3}, {%4,%5}, {%6}, {%0,%1,%2,%3};"
      : "+f"(d[0]), "+f"(d[1]), "+f"(d[2]), "+f"(d[3]) : "r"(a0), "r"(a1), "r"(b0));
}
__device__ __forceinline__ bool elect() { uint32_t p; asm volatile("{.reg .pred p; elect.sync _|p, 0xffffffff; selp.b32 %0,1,0,p;}" : "=r"(p)); return p; }
__device__ __forceinline__ uint32_t pack(float lo, float hi) { uint32_t r; asm("cvt.rn.bf16x2.f32 %0,%1,%2;" : "=r"(r) : "f"(hi), "f"(lo)); return r; }
__device__ __forceinline__ float blo(uint32_t v) { return __uint_as_float(v << 16); }
__device__ __forceinline__ float bhi(uint32_t v) { return __uint_as_float(v & 0xffff0000u); }
__device__ __forceinline__ void lds128(uint32_t& a, uint32_t& b, uint32_t& c, uint32_t& d, uint32_t addr) {
  asm volatile("ld.shared.v4.b32 {%0,%1,%2,%3}, [%4];" : "=r"(a), "=r"(b), "=r"(c), "=r"(d) : "r"(addr) : "memory");
}
__device__ __forceinline__ void sts128(uint32_t addr, uint32_t a, uint32_t b, uint32_t c, uint32_t d) {
  asm volatile("st.shared.v4.b32 [%0], {%1,%2,%3,%4};" ::"r"(addr), "r"(a), "r"(b), "r"(c), "r"(d) : "memory");
}
__device__ __forceinline__ void ldsm4t(uint32_t& a, uint32_t& b, uint32_t& c, uint32_t& d, uint32_t addr) {
  asm volatile("ldmatrix.sync.aligned.m8n8.x4.trans.shared.b16 {%0,%1,%2,%3}, [%4];" : "=r"(a), "=r"(b), "=r"(c), "=r"(d) : "r"(addr) : "memory");
}
__device__ __forceinline__ void ldsm4(uint32_t& a, uint32_t& b, uint32_t& c, uint32_t& d, uint32_t addr) {
  asm volatile("ldmatrix.sync.aligned.m8n8.x4.shared.b16 {%0,%1,%2,%3}, [%4];" : "=r"(a), "=r"(b), "=r"(c), "=r"(d) : "r"(addr) : "memory");
}
__device__ __forceinline__ void stsm4(uint32_t addr, uint32_t a, uint32_t b, uint32_t c, uint32_t d) {
  asm volatile("stmatrix.sync.aligned.m8n8.x4.shared.b16 [%0], {%1,%2,%3,%4};" ::"r"(addr), "r"(a), "r"(b), "r"(c), "r"(d) : "memory");
}
__device__ __forceinline__ void nbar_sync(int id, int n) { asm volatile("bar.sync %0, %1;" ::"r"(id), "r"(n) : "memory"); }
__device__ __forceinline__ void nbar_arrive(int id, int n) { asm volatile("bar.arrive %0, %1;" ::"r"(id), "r"(n) : "memory"); }
#define WG_FENCE() asm volatile("wgmma.fence.sync.aligned;" ::: "memory")
#define WG_COMMIT() asm volatile("wgmma.commit_group.sync.aligned;" ::: "memory")
#define WG_WAIT0() asm volatile("wgmma.wait_group.sync.aligned 0;" ::: "memory")
#define WG_WAIT1() asm volatile("wgmma.wait_group.sync.aligned 1;" ::: "memory")
#define PROXY_FENCE_SMEM() asm volatile("fence.proxy.async.shared::cta;" ::: "memory")
#define PROXY_FENCE_ALL() asm volatile("fence.proxy.async;" ::: "memory")
template <int N> __device__ __forceinline__ void pin(float (&d)[N]) {
#pragma unroll
  for (int i = 0; i < N; i++) asm volatile("" : "+f"(d[i])::"memory");
}
__device__ __forceinline__ void wg64t(float (&d)[32], const uint32_t* a, uint64_t db) {
  asm volatile("wgmma.mma_async.sync.aligned.m64n64k16.f32.bf16.bf16 {%0, %1, %2, %3, %4, %5, %6, %7, %8, %9, %10, %11, %12, %13, %14, %15, %16, %17, %18, %19, %20, %21, %22, %23, %24, %25, %26, %27, %28, %29, %30, %31}, {%32, %33, %34, %35}, %36, 1, 1, 1, 1;"
    : "+f"(d[0]), "+f"(d[1]), "+f"(d[2]), "+f"(d[3]), "+f"(d[4]), "+f"(d[5]), "+f"(d[6]), "+f"(d[7]), "+f"(d[8]), "+f"(d[9]), "+f"(d[10]), "+f"(d[11]), "+f"(d[12]), "+f"(d[13]), "+f"(d[14]), "+f"(d[15]), "+f"(d[16]), "+f"(d[17]), "+f"(d[18]), "+f"(d[19]), "+f"(d[20]), "+f"(d[21]), "+f"(d[22]), "+f"(d[23]), "+f"(d[24]), "+f"(d[25]), "+f"(d[26]), "+f"(d[27]), "+f"(d[28]), "+f"(d[29]), "+f"(d[30]), "+f"(d[31])
    : "r"(a[0]), "r"(a[1]), "r"(a[2]), "r"(a[3]), "l"(db));
}
__device__ __forceinline__ void wg64tz(float (&d)[32], const uint32_t* a, uint64_t db) {
  asm volatile("wgmma.mma_async.sync.aligned.m64n64k16.f32.bf16.bf16 {%0, %1, %2, %3, %4, %5, %6, %7, %8, %9, %10, %11, %12, %13, %14, %15, %16, %17, %18, %19, %20, %21, %22, %23, %24, %25, %26, %27, %28, %29, %30, %31}, {%32, %33, %34, %35}, %36, 0, 1, 1, 1;"
    : "=f"(d[0]), "=f"(d[1]), "=f"(d[2]), "=f"(d[3]), "=f"(d[4]), "=f"(d[5]), "=f"(d[6]), "=f"(d[7]), "=f"(d[8]), "=f"(d[9]), "=f"(d[10]), "=f"(d[11]), "=f"(d[12]), "=f"(d[13]), "=f"(d[14]), "=f"(d[15]), "=f"(d[16]), "=f"(d[17]), "=f"(d[18]), "=f"(d[19]), "=f"(d[20]), "=f"(d[21]), "=f"(d[22]), "=f"(d[23]), "=f"(d[24]), "=f"(d[25]), "=f"(d[26]), "=f"(d[27]), "=f"(d[28]), "=f"(d[29]), "=f"(d[30]), "=f"(d[31])
    : "r"(a[0]), "r"(a[1]), "r"(a[2]), "r"(a[3]), "l"(db));
}
__device__ __forceinline__ void wg64(float (&d)[32], const uint32_t* a, uint32_t dlo) {
  asm volatile("{.reg .b64 db; mov.b64 db, {%36, 8};\n"
    "wgmma.mma_async.sync.aligned.m64n64k16.f32.bf16.bf16 {%0, %1, %2, %3, %4, %5, %6, %7, %8, %9, %10, %11, %12, %13, %14, %15, %16, %17, %18, %19, %20, %21, %22, %23, %24, %25, %26, %27, %28, %29, %30, %31}, {%32, %33, %34, %35}, db, 1, 1, 1, 0;}"
    : "+f"(d[0]), "+f"(d[1]), "+f"(d[2]), "+f"(d[3]), "+f"(d[4]), "+f"(d[5]), "+f"(d[6]), "+f"(d[7]), "+f"(d[8]), "+f"(d[9]), "+f"(d[10]), "+f"(d[11]), "+f"(d[12]), "+f"(d[13]), "+f"(d[14]), "+f"(d[15]), "+f"(d[16]), "+f"(d[17]), "+f"(d[18]), "+f"(d[19]), "+f"(d[20]), "+f"(d[21]), "+f"(d[22]), "+f"(d[23]), "+f"(d[24]), "+f"(d[25]), "+f"(d[26]), "+f"(d[27]), "+f"(d[28]), "+f"(d[29]), "+f"(d[30]), "+f"(d[31])
    : "r"(a[0]), "r"(a[1]), "r"(a[2]), "r"(a[3]), "r"(dlo));
}
__device__ __forceinline__ void wg64z(float (&d)[32], const uint32_t* a, uint32_t dlo) {
  asm volatile("{.reg .b64 db; mov.b64 db, {%36, 8};\n"
    "wgmma.mma_async.sync.aligned.m64n64k16.f32.bf16.bf16 {%0, %1, %2, %3, %4, %5, %6, %7, %8, %9, %10, %11, %12, %13, %14, %15, %16, %17, %18, %19, %20, %21, %22, %23, %24, %25, %26, %27, %28, %29, %30, %31}, {%32, %33, %34, %35}, db, 0, 1, 1, 0;}"
    : "=f"(d[0]), "=f"(d[1]), "=f"(d[2]), "=f"(d[3]), "=f"(d[4]), "=f"(d[5]), "=f"(d[6]), "=f"(d[7]), "=f"(d[8]), "=f"(d[9]), "=f"(d[10]), "=f"(d[11]), "=f"(d[12]), "=f"(d[13]), "=f"(d[14]), "=f"(d[15]), "=f"(d[16]), "=f"(d[17]), "=f"(d[18]), "=f"(d[19]), "=f"(d[20]), "=f"(d[21]), "=f"(d[22]), "=f"(d[23]), "=f"(d[24]), "=f"(d[25]), "=f"(d[26]), "=f"(d[27]), "=f"(d[28]), "=f"(d[29]), "=f"(d[30]), "=f"(d[31])
    : "r"(a[0]), "r"(a[1]), "r"(a[2]), "r"(a[3]), "r"(dlo));
}
__device__ __forceinline__ void wg32(float (&d)[16], const uint32_t* a, uint32_t dlo) {
  asm volatile("{.reg .b64 db; mov.b64 db, {%20, 8};\n"
    "wgmma.mma_async.sync.aligned.m64n32k16.f32.bf16.bf16 {%0, %1, %2, %3, %4, %5, %6, %7, %8, %9, %10, %11, %12, %13, %14, %15}, {%16, %17, %18, %19}, db, 1, 1, 1, 0;}"
    : "+f"(d[0]), "+f"(d[1]), "+f"(d[2]), "+f"(d[3]), "+f"(d[4]), "+f"(d[5]), "+f"(d[6]), "+f"(d[7]), "+f"(d[8]), "+f"(d[9]), "+f"(d[10]), "+f"(d[11]), "+f"(d[12]), "+f"(d[13]), "+f"(d[14]), "+f"(d[15])
    : "r"(a[0]), "r"(a[1]), "r"(a[2]), "r"(a[3]), "r"(dlo));
}
__device__ __forceinline__ void wg32z(float (&d)[16], const uint32_t* a, uint32_t dlo) {
  asm volatile("{.reg .b64 db; mov.b64 db, {%20, 8};\n"
    "wgmma.mma_async.sync.aligned.m64n32k16.f32.bf16.bf16 {%0, %1, %2, %3, %4, %5, %6, %7, %8, %9, %10, %11, %12, %13, %14, %15}, {%16, %17, %18, %19}, db, 0, 1, 1, 0;}"
    : "=f"(d[0]), "=f"(d[1]), "=f"(d[2]), "=f"(d[3]), "=f"(d[4]), "=f"(d[5]), "=f"(d[6]), "=f"(d[7]), "=f"(d[8]), "=f"(d[9]), "=f"(d[10]), "=f"(d[11]), "=f"(d[12]), "=f"(d[13]), "=f"(d[14]), "=f"(d[15])
    : "r"(a[0]), "r"(a[1]), "r"(a[2]), "r"(a[3]), "r"(dlo));
}
}

__device__ __align__(1024) uint16_t g_kvT[D_ * S_];
__device__ __align__(1024) uint16_t g_xT[D_ * S_];
__device__ __align__(1024) uint4 g_st1[512];
__device__ __align__(1024) uint16_t g_hT[2 * D_ * S_];
__device__ __align__(1024) uint4 g_part[16 * 8 * 8 * 1024];
__device__ __align__(1024) unsigned g_cnt[1024 + 1024];
#define TMFLUSH()
#define TC(i)
#define TM(i)
#define TMW(i)

namespace {
constexpr uint32_t SB = 1024;
#define DELAY1 3000
#define DELAY2 2400
#define RSLEEP 60
#define W1PF 1
#define XLATE 3
#define GSPLIT 0
#define NB_ 3
#define HO 2
#define EARLY0 1
#define WARM 0
#define SLATE 0
#define EARLYH 0
#define LIN 12
#define RFW 2
#define PFW 2
#define PFN 2
#define T1 1
#define T2 1
#define N32 4
#define ODDH 1
#define H1W 2
#define XSPLIT 1
#define XORD 1
#define GEARLY 1
#define ST1 0
#define G3S 0
#define WEAK 1
#define SSH 21
#define DSH 14
#define STEPMUL 2097152
#define STR2(x) #x
#define STR(x) STR2(x)
template <int V> struct IC { static constexpr int value = V; };

constexpr int ST_B = 144 * 128;
constexpr int M_RING = 0, M_PARK = 4 * ST_B;
constexpr int M_CONST = M_PARK + 18 * 8192;
constexpr int M_BIAS = M_CONST + 4096, M_B2 = M_BIAS + 576 * 4, M_SMALL = M_B2 + 128 * 4, M_STAT = M_SMALL + 128, M_BAR = M_STAT + 512;
constexpr int CV_P = 8320, CV_PL = 4992, CV_YW = 4224, CV_Y = 4 * CV_YW, XP = 1168, KV_H = 19 * 1152 + 64;
constexpr int C_X = M_RING, C_SK = C_X + 16 * XP, C_KV = C_SK + 4608;
constexpr int C_KVO = M_PARK, C_XO = C_KVO + 5 * 2048, C_P2 = C_XO + 576 * 32, C_PL0 = C_P2 + 2 * CV_P;
constexpr int C_PL1 = M_PARK + 8 * 8192, C_P4 = C_PL1 + 4 * CV_PL;
constexpr int C_PL4 = M_PARK + 12 * 8192, C_Y = C_PL4 + 2 * CV_PL, C_P0 = C_Y + CV_Y;
__device__ __forceinline__ int plane_of(int it) { return it == 4 ? C_PL4 : ((it & 1) ? C_PL1 : C_PL0) + (it >> 1) * 2 * CV_PL; }
__device__ __forceinline__ int pairs_of(int it) { return it == 4 ? C_P4 : (it < 2 ? C_P0 : C_P2) + (it & 1) * CV_P; }
enum { B_FULL = 0, B_EMPTY = 4, B_HINT = 16, B_PL = 23, B_YF = 24, B_YE = 28, B_STEP = 30, B_H = 31, B_SLAB = 32, B_PEER = 33, B_RDY = 35, B_A = 36,
       B_X = 41, B_KV = 42, B_RE = 43, B_KA = 44, B_H1 = 45, B_A7 = 46, B_NB = 47 };
enum Cnt { N_KVA = 0, N_KVB, N_X, N_F, N_H, N_CNT = N_H + 5 };
static_assert(M_BAR % 128 == 0 && C_KV + 2 * KV_H <= M_PARK && C_PL0 + 4 * CV_PL <= C_PL1 && C_P4 + CV_P <= C_PL4 && C_Y + 2 * CV_Y <= M_CONST && 2 * CV_P <= CV_Y && C_PL0 % 128 == 0 && C_XO % 128 == 0, "smem map");
constexpr int M_TM = M_BAR + B_NB * 8, M_SMEM = M_TM + 768;
constexpr uint32_t PEER = 0x1000000u;

__device__ __forceinline__ void grid_arrive(unsigned* c) { asm volatile("red.release.gpu.global.add.u32 [%0], 1;" ::"l"(c) : "memory"); }
__device__ __forceinline__ void grid_wait(const unsigned* p, unsigned target) {
  asm volatile("{\n.reg .pred p;\n.reg .u32 n, v;\n.reg .s32 d;\nmov.u32 n, 0;\nLW:\nld.relaxed.gpu.global.u32 v, [%0];\nsub.s32 d, v, %1;\nsetp.ge.s32 p, d, 0;\n@p bra LD;\n"
               "add.u32 n, n, 1;\nsetp.lt.u32 p, n, 20000;\n@p bra LW;\nLD:\nfence.acquire.gpu;\nfence.proxy.async.global;\n}" ::"l"(p), "r"(target) : "memory");
}

__device__ __forceinline__ void hint_wait(const unsigned* p, unsigned target) {
  asm volatile("{\n.reg .pred p;\n.reg .u32 n, v;\n.reg .s32 d;\nmov.u32 n, 0;\nLW:\nld.relaxed.gpu.global.u32 v, [%0];\nsub.s32 d, v, %1;\nsetp.ge.s32 p, d, 0;\n@p bra LD;\n"
               "add.u32 n, n, 1;\nsetp.lt.u32 p, n, 20000;\n@p bra LW;\nLD:\n}" ::"l"(p), "r"(target) : "memory");
}

__device__ __forceinline__ bool hint_try(const unsigned* p, unsigned target, uint32_t bar, uint32_t ph) {
  uint32_t ok;
  asm volatile("{\n.reg .pred p;\n.reg .u32 n, v;\n.reg .s32 d;\nmov.u32 n, 0;\nLW:\nld.relaxed.gpu.global.u32 v, [%1];\nsub.s32 d, v, %2;\nsetp.ge.s32 p, d, 0;\nselp.u32 %0, 1, 0, p;\n@p bra LD;\n"
               "mbarrier.test_wait.parity.shared::cta.b64 p, [%3], %4;\n@p bra LD;\nadd.u32 n, n, 1;\nsetp.lt.u32 p, n, 20000;\n@p bra LW;\nLD:\n}" : "=r"(ok) : "l"(p), "r"(target), "r"(bar), "r"(ph) : "memory");
  return __all_sync(~0u, ok);
}
template <bool STRONG> __device__ __forceinline__ uint4 ld16(const uint4* p) {
  uint4 v;
  if (STRONG) asm volatile("ld.relaxed.gpu.global.v4.u32 {%0,%1,%2,%3}, [%4];" : "=r"(v.x), "=r"(v.y), "=r"(v.z), "=r"(v.w) : "l"(p) : "memory");
  else asm volatile("ld.global.L1::no_allocate.v4.u32 {%0,%1,%2,%3}, [%4];" : "=r"(v.x), "=r"(v.y), "=r"(v.z), "=r"(v.w) : "l"(p) : "memory");
  return v;
}
__device__ __forceinline__ void hint_add(unsigned* p, unsigned v) { asm volatile("red.relaxed.gpu.global.add.u32 [%0], %1;" ::"l"(p), "r"(v) : "memory"); }
__device__ __forceinline__ uint2 ld_relaxed(const uint2* p) { uint2 v; asm volatile("ld.relaxed.gpu.global.v2.u32 {%0,%1}, [%2];" : "=r"(v.x), "=r"(v.y) : "l"(p) : "memory"); return v; }
__device__ __forceinline__ uint4 ld_relaxed(const uint4* p) { uint4 v; asm volatile("ld.relaxed.gpu.global.v4.u32 {%0,%1,%2,%3}, [%4];" : "=r"(v.x), "=r"(v.y), "=r"(v.z), "=r"(v.w) : "l"(p) : "memory"); return v; }
__device__ __forceinline__ uint32_t bmul(uint32_t a, uint32_t b) { uint32_t r; asm("mul.rn.bf16x2 %0, %1, %2;" : "=r"(r) : "r"(a), "r"(b)); return r; }
__device__ __forceinline__ uint32_t badd(uint32_t a, uint32_t b) { uint32_t r; asm("add.rn.bf16x2 %0, %1, %2;" : "=r"(r) : "r"(a), "r"(b)); return r; }
__device__ __forceinline__ uint32_t bneg(uint32_t a) { uint32_t r; asm("neg.bf16x2 %0, %1;" : "=r"(r) : "r"(a)); return r; }
__device__ __forceinline__ uint32_t bfma(uint32_t a, uint32_t b, uint32_t c) { uint32_t r; asm("fma.rn.bf16x2 %0, %1, %2, %3;" : "=r"(r) : "r"(a), "r"(b), "r"(c)); return r; }
template <bool STRONG = !WEAK> __device__ __forceinline__ void kv_fetch(uint32_t (&u)[8], const uint16_t* p) {
  const uint4 x = ld16<STRONG>((const uint4*)p), y = ld16<STRONG>((const uint4*)(p + 1024));
  u[0] = x.x; u[1] = x.y; u[2] = x.z; u[3] = x.w; u[4] = y.x; u[5] = y.y; u[6] = y.z; u[7] = y.w;
}
__device__ __forceinline__ void kv_place(uint32_t (&u)[8], const uint16_t* p, uint32_t dst) {
  for (int n = 0; (u[0] < 0x10000u || u[4] < 0x10000u) && n < 5000; n++) kv_fetch<true>(u, p);
  __syncwarp();
  u[0] ^= 0xffff0000u; u[4] ^= 0xffff0000u;
  sts128(dst + 16, u[0], u[1], u[2], u[3]); sts128(dst + CV_PL, u[0], u[1], u[2], u[3]);
  sts128(dst + 2048 + 16, u[4], u[5], u[6], u[7]); sts128(dst + 2048 + CV_PL, u[4], u[5], u[6], u[7]);
}

__device__ __forceinline__ void tma3d(uint32_t dst, const CUtensorMap* m, int c0, int c1, int c2, uint32_t bar) {
  asm volatile("cp.async.bulk.tensor.3d.shared::cluster.global.mbarrier::complete_tx::bytes [%0], [%1, {%3, %4, %5}], [%2];" ::"r"(dst), "l"(m), "r"(bar), "r"(c0), "r"(c1), "r"(c2) : "memory");
}
__device__ __forceinline__ int fresh_tid() { int v; asm volatile("mov.u32 %0, %%tid.x;" : "=r"(v)); return v; }
__device__ __forceinline__ int fresh_bid() { int v; asm volatile("mov.u32 %0, %%ctaid.x;" : "=r"(v)); return v; }
__device__ __forceinline__ void tma2d_prefetch(const CUtensorMap* m, int c0, int c1) {
  asm volatile("cp.async.bulk.prefetch.tensor.2d.L2.global [%0, {%1, %2}];" ::"l"(m), "r"(c0), "r"(c1) : "memory");
}
template <int M0, int M1> __device__ __forceinline__ void conv_lda(uint32_t* a, uint32_t pa) {
#pragma unroll
  for (int m = M0; m < M1; m++)
#pragma unroll
    for (int r = 0; r < 4; r++) asm volatile("ld.shared.b32 %0, [%1];" : "=r"(a[4 * m + r]) : "r"(pa + (128 * m + 64 * (r & 1) - 8 * (r >> 1)) * 4) : "memory");
}
template <int C> __device__ __forceinline__ void conv_mma(float (&d)[32], const uint32_t* a, uint32_t db) {
  if (C >= N32) {
    wg64z(d, a, db + 64 * C);
#pragma unroll
    for (int m = 1; m < 4 * (C + 1); m++) wg64(d, a + 4 * m, db + (64 * C - 16 * m));
  } else {
    float (&lo)[16] = *reinterpret_cast<float (*)[16]>(&d[0]);
    float (&hi)[16] = *reinterpret_cast<float (*)[16]>(&d[16]);
    wg32z(lo, a, db + 64 * C); wg32z(hi, a, db + 64 * C + 32);
#pragma unroll
    for (int m = 1; m < 4 * (C + 1); m++) { if (m < 4 * C + 2) wg32(lo, a + 4 * m, db + (64 * C - 16 * m)); wg32(hi, a + 4 * m, db + (64 * C + 32 - 16 * m)); }
  }
}
template <int C> __device__ __forceinline__ void conv_out(const float (&d)[32], float& c0, float& c1, uint32_t ya) {
  uint32_t o[8];
#pragma unroll
  for (int n = 0; n < 8; n++) o[n] = pack(d[4 * n] + (n ? d[4 * n - 2] : c0), d[4 * n + 1] + (n ? d[4 * n - 1] : c1));
  asm volatile("add.f32 %0, %1, 0f80000000;" : "=f"(c0) : "f"(d[30])); asm volatile("add.f32 %0, %1, 0f80000000;" : "=f"(c1) : "f"(d[31]));
#pragma unroll
  for (int i = 0; i < 2; i++)
    asm volatile("stmatrix.sync.aligned.m8n8.x4.trans.shared.b16 [%0], {%1,%2,%3,%4};" ::"r"(ya + C * 1024 + i * 512), "r"(o[4 * i]), "r"(o[4 * i + 1]), "r"(o[4 * i + 2]), "r"(o[4 * i + 3]) : "memory");
}
__device__ __forceinline__ void ssk_fetch(uint32_t (&kq)[12], const uint16_t* row, int t) {
  const uint16_t* src = row + t * 4;
#pragma unroll
  for (int e = 0; e < 4; e++) { asm volatile("ld.global.nc.v2.u32 {%0,%1}, [%2];" : "=r"(kq[2 * e]), "=r"(kq[2 * e + 1]) : "l"(src + e * 512));
    asm volatile("ld.global.nc.u32 %0, [%1];" : "=r"(kq[8 + e]) : "l"(src + e * 512 - ((e == 0 && t == 0) ? 0 : 2))); }
}
__device__ __forceinline__ void build_pairs(uint32_t (&kq)[12], uint32_t dst, int t, float dskip) {
  if (t == 0) { kq[0] = (kq[0] & 0xffff0000u) | (pack(blo(kq[0]) + dskip, 0.f) & 0xffffu); kq[8] = 0; }
  if (t < 2) sts128(dst + t * 16, 0, 0, 0, 0);
#pragma unroll
  for (int e = 0; e < 4; e++) { const uint32_t x = kq[2 * e], y = kq[2 * e + 1];
    sts128(dst + 32 + e * 2048 + t * 16, __byte_perm(x, kq[8 + e], 0x7610), __byte_perm(x, x, 0x1032), __byte_perm(y, x, 0x7610), __byte_perm(y, y, 0x1032)); }
}

__device__ __forceinline__ float gelu2(float x) {
  float u = x * fmaf(x * x, 8.f * 0.035677408136f, 2.f * 0.7978845608f), t;
  asm("tanh.approx.f32 %0,%1;" : "=f"(t) : "f"(u));
  return fmaf(x, t, x);
}
__device__ __forceinline__ void ld_bias(float (&bv)[4], uint32_t ba) {
  asm volatile("ld.shared.v2.f32 {%0,%1}, [%2];" : "=f"(bv[0]), "=f"(bv[1]) : "r"(ba) : "memory");
  asm volatile("ld.shared.v2.f32 {%0,%1}, [%2];" : "=f"(bv[2]), "=f"(bv[3]) : "r"(ba + 32) : "memory");
}
__device__ __forceinline__ void gelu_slice(const float* e, float r0, float r1, float (&bv)[4], uint32_t nba, uint32_t& p0, uint32_t& p1, uint32_t& p2, uint32_t& p3) {
  const float x0 = fmaf(e[0], r0, bv[0]), x1 = fmaf(e[1], r0, bv[1]), x2 = fmaf(e[2], r1, bv[0]), x3 = fmaf(e[3], r1, bv[1]);
  const float x4 = fmaf(e[4], r0, bv[2]), x5 = fmaf(e[5], r0, bv[3]), x6 = fmaf(e[6], r1, bv[2]), x7 = fmaf(e[7], r1, bv[3]);
  ld_bias(bv, nba);
  p0 = pack(gelu2(x0), gelu2(x1)); p1 = pack(gelu2(x2), gelu2(x3)); p2 = pack(gelu2(x4), gelu2(x5)); p3 = pack(gelu2(x6), gelu2(x7));
}
template <int K0, int K1> __device__ __forceinline__ void unpark(uint32_t (&a)[144], uint32_t park0, bool on) {
#pragma unroll
  for (int k = K0; k < K1; k++)
    asm volatile("{.reg .pred p; setp.ne.u32 p, %5, 0; @p ld.shared.v4.b32 {%0,%1,%2,%3}, [%4];}" : "+r"(a[4 * k]), "+r"(a[4 * k + 1]), "+r"(a[4 * k + 2]), "+r"(a[4 * k + 3])
                 : "r"(park0 + (k >> 2) * 16384 + (k & 3) * 2048), "r"((uint32_t)on) : "memory");
}
template <int N0, int N1, int K0, int K1> __device__ __forceinline__ void gelu_last(const float (&e)[32], float r0, float r1, uint32_t ba, uint32_t (&a)[144], uint32_t park0) {
  float bv[6];
#pragma unroll
  for (int n = N0; n < N1; n++) asm volatile("ld.shared.v2.f32 {%0,%1}, [%2];" : "=f"(bv[2 * (n - N0)]), "=f"(bv[2 * (n - N0) + 1]) : "r"(ba + n * 32) : "memory");
  unpark<K0, K1>(a, park0, true);
#pragma unroll
  for (int n = N0; n < N1; n++) { const float b0 = bv[2 * (n - N0)], b1 = bv[2 * (n - N0) + 1];
    a[128 + 2 * n] = pack(gelu2(fmaf(e[4 * n], r0, b0)), gelu2(fmaf(e[4 * n + 1], r0, b1))); a[129 + 2 * n] = pack(gelu2(fmaf(e[4 * n + 2], r1, b0)), gelu2(fmaf(e[4 * n + 3], r1, b1)));
    asm volatile("" : "+r"(a[128 + 2 * n]), "+r"(a[129 + 2 * n])::"memory"); }
}
__device__ __forceinline__ void mma_stage(float (&d)[32], const uint32_t (&a)[144], int sg, uint32_t buf16 = 0) {
  const uint64_t db = mkdesc(SB + M_RING + sg * ST_B, 16384, 1024, 1) + buf16;
  WG_FENCE();
#pragma unroll
  for (int u = 0; u < 9; u++) { if ((sg | u) == 0) wg64tz(d, &a[0], db); else wg64t(d, &a[(sg * 9 + u) * 4], db + u * 128); }
  WG_COMMIT();
}
__device__ __forceinline__ void mma_half(float (&d)[32], const uint32_t (&a)[144], int hf, uint64_t db0) {
  const uint64_t db = db0 + hf * 2 * (ST_B / 16);
  WG_FENCE();
#pragma unroll
  for (int u = 0; u < 18; u++) { if ((hf | u) == 0) wg64tz(d, &a[0], db); else wg64t(d, &a[(hf * 18 + u) * 4], db + u * 128); }
  WG_COMMIT();
}
template <int I0> __device__ __forceinline__ void center(uint32_t (&a)[144], uint32_t n0, uint32_t n1) {
#pragma unroll
  for (int i = I0; i < I0 + 36; i++) asm volatile("sub.rn.bf16x2 %0, %0, %1;" : "+r"(a[i]) : "r"((i & 1) ? n1 : n0));
}
template <bool MAYBE_LAST> __device__ __forceinline__ void chunk1(bool last, float (&d)[32], float (&e)[32], uint32_t (&a)[144], uint32_t bars, uint32_t ph, uint32_t park, uint32_t ba,
                                                                  bool leader, float r0, float r1, float (&bv)[4]) {
#pragma unroll
  for (int sg = 0; sg < 4; sg++) {
    mma_stage(d, a, sg);
    mbar_wait_hot(bars + 8 * (B_FULL + ((sg + 1) & 3)), sg == 3 ? ph ^ 1 : ph);
    if (MAYBE_LAST) { if (sg == 1) unpark<4, 8>(a, park - 7 * 16384, last); if (sg == 2) unpark<8, 13>(a, park - 7 * 16384, last); if (sg == 3) unpark<13, 18>(a, park - 7 * 16384, last); }
    uint32_t p0, p1, p2, p3; gelu_slice(&e[8 * sg], r0, r1, bv, ba + sg * 64 + 64, p0, p1, p2, p3); sts128(park + sg * 2048, p0, p1, p2, p3);
    WG_WAIT0();
    if (leader) mbar_arrive(bars + 8 * (B_EMPTY + sg));
    if (MAYBE_LAST && sg == 0) unpark<0, 4>(a, park - 7 * 16384, last);
  }
  pin(d);
}
__device__ __forceinline__ void ld_part(uint32_t (&u)[16], const char* p) {
#pragma unroll
  for (int i = 0; i < 4; i++) asm volatile("ld.relaxed.gpu.global.v4.u32 {%0,%1,%2,%3}, [%4];" : "=r"(u[4 * i]), "=r"(u[4 * i + 1]), "=r"(u[4 * i + 2]), "=r"(u[4 * i + 3]) : "l"(p + i * 512) : "memory");
}
__device__ __forceinline__ void poll_part(uint32_t (&u)[16], const void* base, uint32_t off, uint32_t step, uint32_t tag) {
  asm volatile("{\n.reg .pred p;\n.reg .u32 n, t, r;\n.reg .u64 a;\nmov.u32 n, 0;\nLW:\nlop3.b32 t, %0, %4, %17, 0x7e;\nlop3.b32 r, %8, %12, %17, 0x7e;\nor.b32 t, t, r;\nand.b32 t, t, 1;\nsetp.eq.u32 p, t, 0;\n@p bra LD;\n"
               "shr.u32 t, n, 31;\nadd.u32 t, t, %19;\nmad.lo.u32 t, t, " STR(STEPMUL) ", %18;\ncvt.u64.u32 a, t;\nadd.u64 a, a, %16;\n"
               "ld.relaxed.gpu.global.v4.u32 {%0,%1,%2,%3}, [a];\nld.relaxed.gpu.global.v4.u32 {%4,%5,%6,%7}, [a+512];\n"
               "ld.relaxed.gpu.global.v4.u32 {%8,%9,%10,%11}, [a+1024];\nld.relaxed.gpu.global.v4.u32 {%12,%13,%14,%15}, [a+1536];\n"
               "add.u32 n, n, 1;\nsetp.lt.u32 p, n, 5000;\n@p bra LW;\nLD:\n}"
               : "+r"(u[0]), "+r"(u[1]), "+r"(u[2]), "+r"(u[3]), "+r"(u[4]), "+r"(u[5]), "+r"(u[6]), "+r"(u[7]), "+r"(u[8]), "+r"(u[9]), "+r"(u[10]), "+r"(u[11]),
                 "+r"(u[12]), "+r"(u[13]), "+r"(u[14]), "+r"(u[15]) : "l"(base), "r"(tag), "r"(off), "r"(step) : "memory");
  __syncwarp();
}
template <int I0, int I1> __device__ __forceinline__ void add_part(float (&s)[32], const uint32_t (&u)[16]) {
#pragma unroll
  for (int i = I0; i < I1; i++) { s[2 * i] += blo(u[i]); s[2 * i + 1] += bhi(u[i]); }
#pragma unroll
  for (int i = 2 * I0; i < 2 * I1; i++) asm volatile("" : "+f"(s[i])::"memory");
}

#define FRESH_IDS() const int tid = fresh_tid(), b = fresh_bid(), lane = tid & 31, tl = tid & 127, g = lane >> 2, t4 = lane & 3, m = b >> 3, j = b & 7, odd = b & 1; \
  const int wp = __shfl_sync(~0u, tid >> 5, 0), wg = wp >> 2, w = wp & 3; const uint32_t sb = SB + (odd << 24), bars = sb + M_BAR; \
  auto chan = [&](int it) { return it < 4 ? b + 128 * it : 512 + (b >> 1); }; \
  auto small_val = [&](int i) { uint32_t v; asm volatile("ld.shared.b32 %0, [%1];" : "=r"(v) : "r"(sb + M_SMALL + i * 4) : "memory"); return v; }; \
  (void)tl; (void)g; (void)t4; (void)m; (void)j; (void)wg; (void)w; (void)bars; (void)chan; (void)small_val

#define LOAD_SLICES() const int hrow = ((small_val(N_F) >> 7) & 1) * D_; \
  auto load_slices = [&](int s0, int s1, uint32_t bar) { mbar_expect(bar, (s1 - s0) * 16384); \
    if (s1 - s0 == 1) tma3d(sb + M_PARK + s0 * 16384, &P.tm_h2, 0, hrow + s0 * 64, 2 * m, bar); \
    else asm volatile("cp.async.bulk.tensor.4d.shared::cluster.global.mbarrier::complete_tx::bytes [%0], [%1, {%3, %3, %4, %5}], [%2];" \
                      ::"r"(sb + M_PARK + s0 * 16384), "l"(&P.tm_h4), "r"(bar), "r"(0), "r"(2 * m), "r"(hrow / 64 + s0) : "memory"); }

struct Params {
  const uint16_t *k, *v, *q, *sk, *ssk, *Dv, *w1, *b1, *w2, *b2;
  uint16_t *out, *kvT, *xT, *hT;
  uint4 *st1, *part; unsigned* cnt; long long* tm;
  CUtensorMap tm_w1, tm_w2, tm_h4, tm_x, tm_kv, tm_h2;
};

__global__ void __launch_bounds__(384, 1) __cluster_dims__(2, 1, 1) k_fused(const __grid_constant__ Params P) {
  extern __shared__ __align__(1024) uint8_t smem_raw[];
  const int tid = threadIdx.x, b = blockIdx.x;
  const uint32_t sb = s2u(smem_raw), bars = sb + M_BAR;
  if (sb != SB + ((b & 1) << 24)) return;
  if (tid == 352) {
    mbar_init(bars + 8 * B_KV, 1);
    asm volatile("fence.mbarrier_init.release.cluster;" ::: "memory");
    const int skip = b ? 0 : 3 * 1152;
    const char *kp = (const char*)P.k + (b * 16 - 3) * 1152, *vp = (const char*)P.v + b * 16 * 1152;
    mbar_expect(bars + 8 * B_KV, 38 * 1152 + 4608 - skip);
    bulk_load(sb + C_KV + skip, kp + skip, 11 * 1152 - skip, bars + 8 * B_KV);
    bulk_load(sb + C_KV + KV_H, kp + 8 * 1152, 11 * 1152, bars + 8 * B_KV);
    bulk_load(sb + C_KV + 11 * 1152, vp, 8 * 1152, bars + 8 * B_KV);
    bulk_load(sb + C_KV + KV_H + 11 * 1152, vp + 8 * 1152, 8 * 1152, bars + 8 * B_KV);
    bulk_load(sb + C_SK, P.sk, 4608, bars + 8 * B_KV);
  }
  const uint32_t tstart = (uint32_t)clock();
  const int wp = __shfl_sync(~0u, tid >> 5, 0), wg = wp >> 2, lane = tid & 31;
  const int j = b & 7;
  auto chan = [&](int it) { return it < 4 ? b + 128 * it : 512 + (b >> 1); };
  if (wp == 9 && lane < 6) asm volatile("prefetch.tensormap [%0];" ::"l"(&P.tm_w1 + lane) : "memory");
  TM(wg);
  if (wp < 10 && elect()) {
    const int i0 = 4 * wp;
    const uint32_t cnt = i0 == B_YF ? 4 : (i0 & ~8) == B_EMPTY ? 2 : 1;
#pragma unroll
    for (int i = 0; i < 4; i++) mbar_init(bars + 8 * (i0 + i), (i < 2 && i0 == B_YE) ? 128 : cnt);
    asm volatile("fence.mbarrier_init.release.cluster;" ::: "memory");
    if (i0 == B_SLAB) { mbar_expect(bars + 8 * B_PEER, 8192); mbar_expect(bars + 8 * (B_PEER + 1), 8192); }
  }
  __syncwarp();
  uint32_t kq[12];
  if (wp == 11) {
    if (elect()) { mbar_init(bars + 8 * B_X, 1); mbar_init(bars + 8 * B_RE, 1); mbar_init(bars + 8 * B_H1, 1); mbar_init(bars + 8 * B_A7, 1); mbar_init(bars + 8 * B_KA, 1); mbar_init(bars + 8 * (B_A + 4), 1); asm volatile("fence.mbarrier_init.release.cluster;" ::: "memory"); mbar_expect(bars + 8 * B_X, 16 * 1152); }
    while ((uint32_t)clock() - tstart < DELAY2) __nanosleep(20);
    __syncwarp();
    nbar_arrive(1, 384);
    if (elect()) {
      while ((uint32_t)clock() - tstart < DELAY1) __nanosleep(20);
#pragma unroll 1
      for (int r = 0; r < 16; r++) bulk_load(sb + C_X + r * XP, P.q + (b * 16 + r) * D_, 1152, bars + 8 * B_X);
    }
    __syncwarp();
    TMW(53);
  } else {
    if (wp < 10) {
      if (wp < 8) { const uint32_t cval = wp < 4 ? 0u : ~0u; sts128(sb + M_CONST + tid * 16, cval, cval, cval, cval); }
      const uint32_t pl = sb + plane_of(wp >> 1) + (wp & 1) * CV_PL + lane * 16;
      sts128(pl, 0, 0, 0, 0); if (lane < 17 - (wp & 1)) sts128(pl + 512, 0, 0, 0, 0);
      PROXY_FENCE_SMEM();
    }
    uint32_t cv = 0, dv = 0;
    if (wp == 10) {
      asm volatile("ld.relaxed.gpu.global.u32 %0, [%1];" : "=r"(cv) : "l"(P.cnt + (lane < 16 ? min(lane, N_CNT - 1) * 32 : 1024 + min(lane & 7, 6) * 128 + b)) : "memory");
      asm volatile("ld.global.nc.u16 %0, [%1];" : "=r"(dv) : "l"(P.Dv + chan(min(lane & 7, 4))) : "memory");
    }
    if (EARLY0 && wp < 4) ssk_fetch(kq, P.ssk + chan(wg) * S_, tid & 127);
    nbar_sync(1, 384);
    if (wp == 10) {
      asm volatile("st.shared.b32 [%0], %1;" ::"r"(sb + M_SMALL + lane * 4), "r"(lane < 16 ? (cv & ~127u) + 128 : lane < 24 ? cv + 8 : dv << 16) : "memory"); TMW(52);
      nbar_arrive(2, 320);
      uint32_t bv[11];
#pragma unroll
      for (int i = 0; i < 11; i++) bv[i] = __ldg((const uint32_t*)(i < 9 ? P.b1 + j * 576 + 64 * i : i == 9 ? P.b2 + j * 64 : P.b2 + 512) + lane);
#pragma unroll
      for (int i = 0; i < 11; i++) { const float f = i < 9 ? 0.5f : 1.f;
        asm volatile("st.shared.v2.f32 [%0], {%1,%2};" ::"r"(sb + M_BIAS + i * 256 + lane * 8), "f"(f * blo(bv[i])), "f"(f * bhi(bv[i])) : "memory"); }
    }
    if (wp < 9) {
      {
        const int half = lane & 1, c0 = wp * 64 + (lane >> 1) * 4;
        uint32_t s0[4], s1[4];
        uint2 kr[11], vr[8];
        const uint32_t ka = sb + C_KV + half * KV_H + c0 * 2;
        if (wp < 8 && !(EARLY0 && wp < 4)) ssk_fetch(kq, P.ssk + chan(wg) * S_, tid & 127);
        if (wp >= 4) nbar_sync(2, 320);
        mbar_wait(bars + 8 * B_KV, 0);
        if (wg == 0) TM(50);
        lds128(s0[0], s0[1], s0[2], s0[3], sb + C_SK + c0 * 8); lds128(s1[0], s1[1], s1[2], s1[3], sb + C_SK + c0 * 8 + 16);
#pragma unroll
        for (int r = 0; r < 11; r++) asm volatile("ld.shared.v2.b32 {%0,%1}, [%2];" : "=r"(kr[r].x), "=r"(kr[r].y) : "r"(ka + r * 1152) : "memory");
#pragma unroll
        for (int r = 0; r < 8; r++) asm volatile("ld.shared.v2.b32 {%0,%1}, [%2];" : "=r"(vr[r].x), "=r"(vr[r].y) : "r"(ka + (11 + r) * 1152) : "memory");
        uint32_t wa[4], wb[4];
        wa[0] = __byte_perm(s0[0], s0[2], 0x5410); wa[1] = __byte_perm(s0[0], s0[2], 0x7632); wa[2] = __byte_perm(s0[1], s0[3], 0x5410); wa[3] = __byte_perm(s0[1], s0[3], 0x7632);
        wb[0] = __byte_perm(s1[0], s1[2], 0x5410); wb[1] = __byte_perm(s1[0], s1[2], 0x7632); wb[2] = __byte_perm(s1[1], s1[3], 0x5410); wb[3] = __byte_perm(s1[1], s1[3], 0x7632);
        if (b == 0 && half == 0) { kr[0] = kr[1] = kr[2] = make_uint2(0, 0); }
#pragma unroll
        for (int r = 0; r < 8; r++) {
          vr[r].x = bmul(bfma(kr[r + 3].x, wa[0], bfma(kr[r + 2].x, wa[1], bfma(kr[r + 1].x, wa[2], bmul(kr[r].x, wa[3])))), vr[r].x);
          vr[r].y = bmul(bfma(kr[r + 3].y, wb[0], bfma(kr[r + 2].y, wb[1], bfma(kr[r + 1].y, wb[2], bmul(kr[r].y, wb[3])))), vr[r].y);
        }
        uint4* dst = (uint4*)(P.kvT + c0 * S_ + 16 * b + 8 * half);
        const uint32_t stg = sb + C_KVO + (wp - 4) * 2048;
#pragma unroll
        for (int c = 0; c < 4; c++) {
          uint32_t o[4];
#pragma unroll
          for (int i = 0; i < 4; i++) o[i] = __byte_perm((c & 2) ? vr[2 * i].y : vr[2 * i].x, (c & 2) ? vr[2 * i + 1].y : vr[2 * i + 1].x, (c & 1) ? 0x7632 : 0x5410);
          if (wp < 4) { asm volatile("st.relaxed.gpu.global.v4.u32 [%0], {%1,%2,%3,%4};" ::"l"(dst + c * (S_ / 8)), "r"(o[0] ^ 0xffff0000u), "r"(o[1]), "r"(o[2]), "r"(o[3]) : "memory"); }
          else sts128(stg + c * 512 + lane * 16, o[0] ^ 0xffff0000u, o[1], o[2], o[3]);
        }
        if (wp < 4) { nbar_sync(2, 320); if (wp == 0 && elect()) hint_add(P.cnt + N_KVA * 32, 1); }
        TM(48 + (wg != 0));
      }
    }
    if (wp >= 4 && wp < 9 && wp != 7) nbar_arrive(7, 160);
    if (wp == 7) {
      nbar_sync(7, 160);
      if (elect()) {
        PROXY_FENCE_SMEM();
#pragma unroll 1
        for (int i = 4; i < 9; i++) asm volatile("cp.async.bulk.tensor.3d.global.shared::cta.bulk_group [%0, {%2, %3, %4}], [%1];" ::"l"(&P.tm_kv), "r"(sb + C_KVO + (i - 4) * 2048), "r"(16 * b), "r"(i * 16), "r"(0) : "memory");
        asm volatile("cp.async.bulk.commit_group;" ::: "memory"); asm volatile("cp.async.bulk.wait_group.read 0;" ::: "memory");
        hint_add(P.cnt + N_KVB * 32, 1);
      }
      __syncwarp();
      TMW(51);
    }
  }
  if (wg == 2) {
    asm volatile("setmaxnreg.dec.sync.aligned.u32 136;");
    {
    FRESH_IDS();
    const int pw = w;
    {
      const uint32_t xa = sb + C_X + (lane & 15) * XP + (w * 144 + (lane >> 4) * 8) * 2;
      const uint32_t xb = sb + C_X + (4 * ((lane & 7) >> 1) + (lane & 1) + ((lane >> 2) & 2)) * XP + (w * 144 + (lane >> 4) * 8) * 2;
      const uint32_t xo = sb + C_XO + w * 144 * 32, enc = (lane & 1) ? 0u : 0xffff0000u;
      float sa[4] = {0.f, 0.f, 0.f, 0.f}, g0[4] = {0.f, 0.f, 0.f, 0.f}, g1[4] = {0.f, 0.f, 0.f, 0.f}, g2[4] = {0.f, 0.f, 0.f, 0.f}, g3[4] = {0.f, 0.f, 0.f, 0.f};
      mbar_wait(bars + 8 * B_X, 0);
      TM(17);
      uint32_t p0, p1, f[36], t[36];
      asm volatile("ld.shared.u16 %0, [%1];" : "=r"(p0) : "r"(sb + C_X + g * XP) : "memory"); asm volatile("ld.shared.u16 %0, [%1];" : "=r"(p1) : "r"(sb + C_X + (g + 8) * XP) : "memory");
#pragma unroll
      for (int k = 0; k < 9; k++) ldsm4(f[4 * k], f[4 * k + 1], f[4 * k + 2], f[4 * k + 3], xa + k * 32);
#pragma unroll
      for (int k = 0; k < 9; k++) ldsm4t(t[4 * k], t[4 * k + 1], t[4 * k + 2], t[4 * k + 3], xb + k * 32);
      p0 *= 0x10001u; p1 *= 0x10001u;
#pragma unroll
      for (int k = 0; k < 9; k++) {
#pragma unroll
        for (int i = 0; i < 4; i++) asm("sub.rn.bf16x2 %0, %0, %1;" : "+r"(f[4 * k + i]) : "r"((i & 1) ? p1 : p0));
        mma16816(sa, &f[4 * k], 0x3f803f80u, 0x3f803f80u);
        mma1688(g0, f[4 * k], f[4 * k + 1], f[4 * k]); mma1688(g1, f[4 * k], f[4 * k + 1], f[4 * k + 1]);
        mma1688(g2, f[4 * k + 2], f[4 * k + 3], f[4 * k + 2]); mma1688(g3, f[4 * k + 2], f[4 * k + 3], f[4 * k + 3]);
        asm volatile("st.shared.v2.b32 [%0], {%1,%2};" ::"r"(xo + k * 512 + lane * 8), "r"(t[4 * k] ^ enc), "r"(t[4 * k + 1]) : "memory");
        asm volatile("st.shared.v2.b32 [%0], {%1,%2};" ::"r"(xo + k * 512 + 256 + lane * 8), "r"(t[4 * k + 2] ^ enc), "r"(t[4 * k + 3]) : "memory"); }
      if (t4 == (g >> 1)) asm volatile("st.shared.v4.f32 [%0], {%1,%2,%3,%4};" ::"r"(sb + M_STAT + g * 64 + w * 16), "f"(sa[0]), "f"(sa[2]),
                                       "f"((g & 1) ? g0[1] + g2[1] : g0[0] + g2[0]), "f"((g & 1) ? g1[3] + g3[3] : g1[2] + g3[2]) : "memory");
      nbar_arrive(13, 256);
      nbar_sync(5, 128);
      TM(5);
      if (w == 0) {
        uint32_t q[4]; lds128(q[0], q[1], q[2], q[3], sb + M_STAT + lane * 16);
        float e0 = __uint_as_float(q[0]), e1 = __uint_as_float(q[1]), v0 = __uint_as_float(q[2]), v1 = __uint_as_float(q[3]);
#pragma unroll
        for (int o = 1; o < 4; o <<= 1) { e0 += __shfl_xor_sync(~0u, e0, o); e1 += __shfl_xor_sync(~0u, e1, o); v0 += __shfl_xor_sync(~0u, v0, o); v1 += __shfl_xor_sync(~0u, v1, o); }
        e0 *= 1.f / D_; e1 *= 1.f / D_;
        const uint32_t rp = pack(rsqrtf(fmaxf(fmaf(-e0, e0, v0 * (1.f / D_)), 0.f) + 1e-5f), rsqrtf(fmaxf(fmaf(-e1, e1, v1 * (1.f / D_)), 0.f) + 1e-5f));
        const uint32_t np = pack(-(e0 + blo(p0)) * blo(rp), -(e1 + blo(p1)) * bhi(rp));
        const uint32_t mine = (t4 & 2) ? np : rp;
        uint32_t o[4];
#pragma unroll
        for (int i = 0; i < 4; i++) o[i] = __byte_perm(__shfl_sync(~0u, mine, 8 * i + t4), __shfl_sync(~0u, mine, 8 * i + 4 + t4), (t4 & 1) ? 0x7632 : 0x5410);
        if (lane < 4) asm volatile("st.relaxed.gpu.global.v4.u32 [%0], {%1,%2,%3,%4};" ::"l"(P.st1 + (lane >> 1) * 256 + 2 * b + (lane & 1)), "r"(o[0] ^ 0xffff0000u), "r"(o[1]), "r"(o[2]), "r"(o[3]) : "memory");
        nbar_arrive(0, 64);
      } else if (w == 1) {
        if (XLATE) nbar_sync(12, 160);
        if (lane == 0) { PROXY_FENCE_SMEM();
#pragma unroll 1
          for (int i = 0; i < 9; i++) { tma2d_store(&P.tm_x, sb + C_XO + i * 2048, 16 * b, i * 64); if (i == 3 || i == 8) asm volatile("cp.async.bulk.commit_group;" ::: "memory"); }
          if (XSPLIT) asm volatile("cp.async.bulk.wait_group.read 1;" ::: "memory"); else asm volatile("cp.async.bulk.wait_group.read 0;" ::: "memory"); }
        __syncwarp();
        nbar_sync(0, 64);
        if (lane == 0) { hint_add(P.cnt + N_X * 32, 1); asm volatile("cp.async.bulk.wait_group.read 0;" ::: "memory"); hint_add(P.cnt + N_H * 32, 1); }
        __syncwarp();
        TMW(18);
      }
    }
    LOAD_SLICES();
    {
      const uint32_t yr = sb + C_Y + tl * 16;
      const uint4 *xp = (const uint4*)P.xT + b * 256 + tl, *xp4 = (const uint4*)P.xT + chan(4) * 256 + tl, *sp = P.st1 + tl;
      uint4 *hp = (uint4*)P.hT + (hrow + b) * 256 + tl, *hp4 = (uint4*)P.hT + (hrow + chan(4)) * 256 + tl;
      asm volatile("" : "+l"(xp), "+l"(xp4), "+l"(sp), "+l"(hp), "+l"(hp4));
      uint4 st[4], xv[10];
      uint32_t z[4][4];
      auto load_x = [&](auto ST, int part) {
#pragma unroll
        for (int i = 0; i < 4; i++) if (part == 0) st[i] = ld16<decltype(ST)::value>(sp + i * 128);
#pragma unroll
        for (int i = 0; i < 10; i++) if ((i >= 4) == part) xv[i] = ld16<decltype(ST)::value>((i < 8 ? xp + (i >> 1) * 128 * 256 : xp4) + (i & 1) * 128);
      };
      auto check_x = [&](int part) {
#pragma unroll 1
        for (int n = 0; n < 5000; n++) {
          uint32_t mn = part ? 0xffffffffu : min(min(st[0].x, st[1].x), min(st[2].x, st[3].x));
#pragma unroll
          for (int i = 0; i < 10; i++) if ((i >= 4) == part) mn = min(mn, xv[i].x);
          if (mn >= 0x10000u) break;
          load_x(IC<1>{}, part);
        }
        __syncwarp();
      };
      auto yf = [&](int u) { return bars + 8 * (B_YF + (u & 1) * 2 + ((u >> 1) & 1)); };
      auto sum = [&](int u) {
        const int hf = u & 1, g2 = (u >> 1) & 1;
        uint32_t y[16];
        mbar_wait(yf(u), (u >> 2) & 1);
#pragma unroll
        for (int ww = 0; ww < 4; ww++) lds128(y[4 * ww], y[4 * ww + 1], y[4 * ww + 2], y[4 * ww + 3], yr + g2 * CV_Y + hf * 2048 + ww * CV_YW);
#pragma unroll
        for (int r = 0; r < 4; r++) z[u & 3][r] = badd(badd(y[r], y[4 + r]), badd(y[8 + r], y[12 + r]));
        asm volatile("" : "+r"(z[u & 3][0]), "+r"(z[u & 3][1]), "+r"(z[u & 3][2]), "+r"(z[u & 3][3])::"memory");
        if (hf && u < 6) mbar_arrive(bars + 8 * (B_YE + g2));
      };
      auto gate = [&](int u, bool on) {
        const int hf = u & 1;
        const uint4 r = st[hf], n = st[2 + hf], x = xv[u];
        const uint32_t x0 = x.x ^ 0xffff0000u;
        const uint4 h = make_uint4(bfma(bfma(x0, r.x, n.x), z[u & 3][0], x0), bfma(bfma(x.y, r.y, n.y), z[u & 3][1], x.y), bfma(bfma(x.z, r.z, n.z), z[u & 3][2], x.z), bfma(bfma(x.w, r.w, n.w), z[u & 3][3], x.w));
        if (on) __stcg((u < 8 ? hp + (u >> 1) * 128 * 256 : hp4) + hf * 128, h);
      };
      auto publish = [&](int it) { const int id = it < 3 ? 9 + it : 15; if (pw) nbar_arrive(id, 128); else { nbar_sync(id, 128); if (elect()) hint_add(P.cnt + (N_H + it) * 32, 1); __syncwarp(); } };
      auto fills = [&](int when) {
        if (when == PFW && pw == 2 && elect()) { if (PFN == 0) l2_prefetch(P.w1 + b * 20736, 41472); else if (m < 4 * PFN) tma2d_prefetch(&P.tm_w1, j * 576 + (1 + (m >> 2)) * 64, (m & 3) * 144); }
        if (when == RFW && pw == 3 && elect()) {
          if (when == 0) mbar_wait(bars + 8 * B_PL, 0);
#pragma unroll 1
          for (int sg = 0; sg < 4; sg++) { mbar_expect(bars + 8 * (B_FULL + sg), ST_B); tma2d(sb + M_RING + sg * ST_B, &P.tm_w1, j * 576, sg * 144, bars + 8 * (B_FULL + sg)); } }
        __syncwarp();
      };
      fills(0);
      sum(0);
      if (XORD == 0) {
        const bool got = hint_try(P.cnt + N_X * 32, small_val(N_X), yf(1), 0);
        if (!got) { uint32_t h0;
          asm volatile("ld.relaxed.gpu.global.u32 %0, [%1];" : "=r"(h0) : "l"(P.cnt + N_X * 32) : "memory");
          sum(1); if ((int)(h0 - small_val(N_X)) < 0) hint_wait(P.cnt + N_X * 32, small_val(N_X)); __syncwarp(); }
        load_x(IC<!WEAK>{}, 0);
        TM(7);
        fills(1);
        if (got) sum(1);
      } else {
        hint_wait(P.cnt + N_X * 32, small_val(N_X)); __syncwarp();
        load_x(IC<!WEAK>{}, 0);
        TM(7);
        fills(1);
        sum(1);
      }
      uint32_t hx = 0;
      if (XSPLIT) asm volatile("ld.relaxed.gpu.global.u32 %0, [%1];" : "=r"(hx) : "l"(P.cnt + N_H * 32) : "memory");
      if (!GEARLY) { sum(2); sum(3); }
      check_x(0);
      if (!XSPLIT) load_x(IC<!WEAK>{}, 1);
#pragma unroll
      for (int i = 0; i < 4; i++) st[i].x ^= 0xffff0000u;
      TM(11);
      gate(0, true); gate(1, true);
      if (GEARLY) sum(2);
      gate(2, true);
      if (GEARLY) sum(3);
      gate(3, true); publish(1);
      if (XSPLIT) { if ((int)(hx - small_val(N_H)) < 0) hint_wait(P.cnt + N_H * 32, small_val(N_H)); __syncwarp(); load_x(IC<!WEAK>{}, 1); }
      fills(2);
      TM(9);
      sum(4); check_x(1); gate(4, true); sum(5); gate(5, true); publish(2);
      TM(54);
      fills(3);
      uint32_t hv = 0;
      if (H1W == 2) asm volatile("ld.relaxed.gpu.global.u32 %0, [%1];" : "=r"(hv) : "l"(P.cnt + (N_H + 1) * 32) : "memory");
      sum(6); gate(6, true);
      if (H1W && pw == 2) {
        const bool ok = H1W == 2 ? (int)(hv - small_val(N_H + 1)) >= 0 : hint_try(P.cnt + (N_H + 1) * 32, small_val(N_H + 1), yf(7), 1);
        if (elect()) {
          if (ok) { asm volatile("fence.proxy.async.global;" ::: "memory"); load_slices(0, 2, bars + 8 * B_A); load_slices(2, 4, bars + 8 * (B_A + 1)); }
          asm volatile("st.shared.b32 [%0], %1;" ::"r"(sb + M_SMALL + 15 * 4), "r"((uint32_t)ok) : "memory"); mbar_arrive(bars + 8 * B_H1); }
        __syncwarp();
      }
      sum(7); gate(7, true); publish(3);
      TM(55);
      fills(4);
      if (!odd) { sum(8); gate(8, true); }
      sum(9); gate(9, (tl >= 64) == odd);
      TM(10);
      nbar_sync(5, 128);
      if (pw == 0 && elect()) hint_add(P.cnt + (N_H + 4) * 32, 1);
      __syncwarp();
    }
    }
    asm volatile("setmaxnreg.dec.sync.aligned.u32 24;");
    FRESH_IDS();
    const int pw = w;
    LOAD_SLICES();
    auto fetch_late = [&](int it) {
      if (elect()) { hint_wait(P.cnt + (N_H + it) * 32, small_val(N_H + it)); asm volatile("fence.proxy.async.global;" ::: "memory"); if (G3S && it == 3) { load_slices(6, 7, bars + 8 * (B_A + 3)); load_slices(7, 8, bars + 8 * B_A7); } else load_slices(2 * it, it < 4 ? 2 * it + 2 : 9, bars + 8 * (B_A + it)); }
      __syncwarp();
      TMW(17 - it); };
    if (pw == 0) {
#pragma unroll 1
      for (int c = 1; c < 9; c++) {
#pragma unroll
        for (int sg = 0; sg < 4; sg++) {
          mbar_wait(bars + 8 * (B_EMPTY + sg), (c & 1) ^ 1);
          if (elect()) { mbar_expect(bars + 8 * (B_FULL + sg), ST_B); tma2d(sb + M_RING + sg * ST_B, &P.tm_w1, j * 576 + c * 64, sg * 144, bars + 8 * (B_FULL + sg)); }
          __syncwarp();
        }
      }
#pragma unroll 1
      for (int s = 0; s < 9; s++) {
        const uint32_t bb = bars + (s & 1) * 64, dst = sb + (s & 1) * M_PARK, ph = ((s >> 1) ^ s) & 1;
        const int col = (s == 0 ? 8 : (j ^ (8 - s))) * 64;
#pragma unroll
        for (int sg = 0; sg < 4; sg++) {
          mbar_wait(s == 1 ? bars + 8 * (B_EMPTY + (sg >> 1)) : bb + 8 * (B_EMPTY + sg), ph);
          if (elect()) { mbar_expect(bb + 8 * (B_FULL + sg), ST_B); tma2d(dst + sg * ST_B, &P.tm_w2, col, j * 576 + sg * 144, bb + 8 * (B_FULL + sg)); }
          __syncwarp();
        }
      }
    } else if (pw == 3) {
      fetch_late(4);
      if (elect()) {
        const uint16_t* pf = P.w2 + (j * 576 + m * 36) * D_;
#pragma unroll 1
        for (int p = 0; p < 9; p++) {
          mbar_wait_long(bars + 8 * (B_EMPTY + 1), p & 1);
          const int o = chan(p >> 1) * S_ + (p < 8 ? p & 1 : odd) * 1024;
          if (PFN && p + PFN + 1 < 9 && (m >> 2) == (p & 3)) tma2d_prefetch(&P.tm_w1, j * 576 + (p + PFN + 1) * 64, (m & 3) * 144);
          if (p < 8) l2_prefetch(pf + p * 2592, 5184);
          bulk_store(P.kvT + o, sb + M_CONST, 2048); bulk_store(P.xT + o, sb + M_CONST, 2048); bulk_store(P.hT + (D_ - hrow) * S_ + o, sb + M_CONST + 2048, 2048);
        }
        bulk_store(P.st1 + 2 * b, sb + M_CONST, 32); bulk_store(P.st1 + 256 + 2 * b, sb + M_CONST, 32);
        asm volatile("cp.async.bulk.commit_group;" ::: "memory"); asm volatile("cp.async.bulk.wait_group.read 0;" ::: "memory");
        mbar_wait(bars + 8 * (B_EMPTY + 3), 0); mbar_wait_long(bars + 8 * (B_EMPTY + 2), 1); mbar_wait(bars + 8 * (B_EMPTY + 3), 1);
        mbar_arrive(bars + 8 * B_STEP);
      }
      __syncwarp();
#pragma unroll 1
      for (int t = 0; t < 7; t++) {
        unsigned* hp = P.cnt + 1024 + t * 128 + (t == 0 ? (b & ~7) + (lane & 7) : b ^ (8 - t));
        if (t) { mbar_wait_long(bars + (t & 1) * 64 + 8 * B_EMPTY, ((t >> 1) ^ t ^ 1) & 1); mbar_wait(bars + (t & 1) * 64 + 8 * (B_EMPTY + 3), ((t >> 1) ^ t ^ 1) & 1); }
        if (lane < (t == 0 ? 8 : 1)) hint_add(hp, t == 0 ? 1 : 8);
        __syncwarp();
      }
    } else if (pw == 2) {
      fetch_late(3);
      mbar_wait_long(bars + 8 * B_STEP, 0);
#pragma unroll 1
      for (int s = 0; s < 7; s++) {
        if (lane == s) { hint_wait(P.cnt + 1024 + s * 128 + b, small_val(16 + s)); mbar_arrive(bars + 8 * (B_HINT + s)); }
        __syncwarp();
      }
    } else {
      if (elect()) { grid_arrive(P.cnt + N_F * 32); mbar_wait(bars + 8 * (B_EMPTY + 3), 0); grid_wait(P.cnt + N_F * 32, small_val(N_F));
        mbar_expect(bars + 8 * B_H, 16384); tma3d(sb + M_PARK + 8 * 16384, &P.tm_h2, 0, hrow + j * 64, 2 * m, bars + 8 * B_H); }
      __syncwarp();
      mbar_wait_long(bars + 8 * B_STEP, 0);
      if (elect()) {
        asm volatile("fence.proxy.async.global;" ::: "memory");
        mbar_expect(bars + 8 * B_KA, 16384);
        tma3d(sb + M_PARK + 5 * 16384, &P.tm_h2, 0, hrow + 512, 2 * m, bars + 8 * B_KA);
        asm volatile("mbarrier.arrive.release.cluster.shared::cluster.b64 _, [%0];" ::"r"((bars ^ PEER) + 8 * B_RDY) : "memory");
      }
      __syncwarp();
      mbar_wait(bars + 8 * B_HINT, 0);
      mbar_wait(bars + 8 * B_KA, 0);
#pragma unroll 1
      for (int it = 0; it < 2000; it++) {
        if (elect()) { mbar_expect(bars + 8 * B_SLAB, 16384); bulk_load(sb + M_PARK + 7 * 16384, P.part + (b << (DSH - 4)), 16384, bars + 8 * B_SLAB); }
        __syncwarp();
        mbar_wait(bars + 8 * B_SLAB, it & 1);
        uint32_t bad = 0;
#pragma unroll 1
        for (int i = 0; i < 8; i++) {
          const int ln = (fresh_tid() + (i >> 8)) & 31;
          float sm[4];
          uint32_t u0, u1;
          asm volatile("ldmatrix.sync.aligned.m8n8.x2.trans.shared.b16 {%0,%1}, [%2];" : "=r"(u0), "=r"(u1)
                       : "r"(sb + M_PARK + (10 + (j >> 2)) * 8192 + i * 1024 + (ln & 7) * 128 + (((((ln >> 3) & 1) + 2 * (j & 3)) ^ (ln & 7)) * 16)) : "memory");
          asm volatile("ld.shared.v2.f32 {%0,%1}, [%2];" : "=f"(sm[0]), "=f"(sm[1]) : "r"(sb + M_B2 + 256 + (ln & 3) * 8 + i * 32) : "memory");
          sm[2] = sm[0] + blo(u1); sm[3] = sm[1] + bhi(u1); sm[0] += blo(u0); sm[1] += bhi(u0);
          const uint32_t pa = sb + M_PARK + 7 * 16384 + (i >> 1) * 512 + (i & 1) * 8 + ln * 16, tg = (hrow >> 6) & ~i & 1;
#pragma unroll 2
          for (int src = 0; src < 8; src++) {
            asm volatile("ld.shared.v2.b32 {%0,%1}, [%2];" : "=r"(u0), "=r"(u1) : "r"(pa + src * 2048) : "memory");
            u0 ^= tg; bad |= u0 & ~i;
            sm[0] += blo(u0); sm[1] += bhi(u0); sm[2] += blo(u1); sm[3] += bhi(u1);
          }
          uint16_t* op = P.out + (b * 16 + (ln >> 2)) * D_ + 512 + 2 * (ln & 3) + i * 8;
          *(uint32_t*)op = pack(sm[0], sm[1]); *(uint32_t*)(op + 8 * D_) = pack(sm[2], sm[3]);
        }
        if (!__any_sync(~0u, bad & 1)) break;
      }
    }
  } else {
    {
      FRESH_IDS();
      uint32_t a0[64];
      TM(57);
      const uint32_t pofs = sb + (8 + 16 * w + g + 8 - 2 * t4) * 4;
      const uint32_t ya = sb + C_Y + wg * CV_Y + w * (CV_YW + 32) + lane * 16;
      const uint32_t bfull = bars + 8 * (B_YF + wg);
      uint32_t u[8];
      {
        build_pairs(kq, sb + pairs_of(wg), tl, __uint_as_float(small_val(24 + wg)));
        uint32_t kn[3][12];
        const uint16_t *sr = P.ssk + (b + 256) * S_, *sr4 = P.ssk + chan(4) * S_;
        asm volatile("" : "+l"(sr), "+l"(sr4));
        if (wg && !SLATE) { ssk_fetch(kn[0], sr, tl); ssk_fetch(kn[1], sr + 128 * S_, tl); ssk_fetch(kn[2], sr4, tl); }
        nbar_sync(3 + wg, 128);
        conv_lda<0, 16>(a0, pofs + pairs_of(wg));
        asm volatile("setmaxnreg.inc.sync.aligned.u32 184;");
        TM(16);
        if (wp == 0) hint_wait(P.cnt + N_KVA * 32, small_val(N_KVA));
        if (wg) nbar_sync(6, 256); else { nbar_arrive(6, 256); nbar_sync(3, 128); }
        TM(3 + wg);
        kv_fetch(u, P.kvT + chan(wg) * S_ + tl * 8);
        if (XLATE == 3 && wg == 0) nbar_arrive(12, 160);
        if (wg && SLATE) { ssk_fetch(kn[0], sr, tl); ssk_fetch(kn[1], sr + 128 * S_, tl); ssk_fetch(kn[2], sr4, tl); }
        if (lane < 2 * w) sts128(ya - 32 * w, 0, 0, 0, 0);
        if (wg) {
          if (w == 0) { hint_wait(P.cnt + N_KVB * 32, small_val(N_KVB)); __syncwarp(); if (elect()) mbar_arrive(bars + 8 * B_PL); __syncwarp(); }
#pragma unroll
          for (int i = 0; i < 3; i++) build_pairs(kn[i], sb + pairs_of(2 + i), tl, __uint_as_float(small_val(26 + i)));
          nbar_arrive(1, 256);
          TM(56);
        }
      }
#pragma unroll 1
      for (int it = wg; it < 5; it += 2) {
        kv_place(u, P.kvT + chan(it) * S_ + tl * 8, sb + plane_of(it) + 768 + tl * 16);
        if (XLATE == 1 && it == 0) nbar_arrive(12, 160);
        PROXY_FENCE_SMEM();
        const uint32_t db = (uint32_t)mkdesc(SB + plane_of(it) + 768, CV_PL, 128, 0);
        mbar_wait(bfull + 32, ((it >> 1) & 1) ^ 1);
        nbar_sync(13 + wg, 256);
        if (it < 2) TM(19 + wg * 16);
        float c0 = 0.f, c1 = 0.f;
        const uint32_t pa = pofs + pairs_of(it);
        if (it == 4 && odd) {
          float d[32], e[32];
          if (LIN) { conv_lda<LIN, 16>(a0, pa); nbar_arrive(2, 256); }
          if (ODDH) {
            float f[16];
            WG_FENCE(); wg32z(f, a0, db + 160);
#pragma unroll
            for (int mm = 1; mm < 12; mm++) wg32(f, a0 + 4 * mm, db + 160 - 16 * mm);
            conv_mma<3>(e, a0, db); WG_COMMIT();
            WG_WAIT0(); pin(f); pin(e);
            asm volatile("stmatrix.sync.aligned.m8n8.x1.trans.shared.b16 [%0], {%1};" ::"r"(ya + 2 * 1024 + 7 * 128), "r"(pack(f[12] + f[10], f[13] + f[11])) : "memory");
            c0 = f[14]; c1 = f[15];
            conv_out<3>(e, c0, c1, ya);
          } else {
          WG_FENCE(); conv_mma<2>(d, a0, db); conv_mma<3>(e, a0, db); WG_COMMIT();
          WG_WAIT0(); pin(d); pin(e);
          conv_out<2>(d, c0, c1, ya); conv_out<3>(e, c0, c1, ya);
          }
        } else {
          float d[32], e[32];
          WG_FENCE(); conv_mma<0>(d, a0, db); WG_COMMIT(); conv_mma<1>(e, a0, db); WG_COMMIT();
          if (HO == 0 && it < 4) nbar_arrive(13 + (wg ^ 1), 256);
          if (LIN == 8 && it >= 2) conv_lda<8, 12>(a0, pa);
          if (LIN && it == 4) nbar_arrive(2, 256);
          WG_WAIT1(); pin(d);
          conv_out<0>(d, c0, c1, ya);
          WG_FENCE(); conv_mma<2>(d, a0, db); WG_COMMIT();
          if (HO == 1 && it < 4) nbar_arrive(13 + (wg ^ 1), 256);
          if (LIN && (it == 2 || it == 3)) conv_lda<12, 16>(a0, pa);
          WG_WAIT1(); pin(e);
          conv_out<1>(e, c0, c1, ya);
          __syncwarp();
          if (lane == 0) mbar_arrive(bfull);
          if (it == 4) { WG_WAIT0(); pin(d); conv_out<2>(d, c0, c1, ya); }
          else {
            if (HO == 2) nbar_arrive(13 + (wg ^ 1), 256);
            WG_FENCE(); conv_mma<3>(e, a0, db); WG_COMMIT();
            if (HO == 3) nbar_arrive(13 + (wg ^ 1), 256);
            if (it < 3) { mbar_wait(bars + 8 * B_PL, 0); kv_fetch(u, P.kvT + chan(it + 2) * S_ + tl * 8); }
            WG_WAIT0(); pin(d); pin(e);
            conv_out<2>(d, c0, c1, ya); conv_out<3>(e, c0, c1, ya);
          }
        }
        __syncwarp();
        if (lane == 0) mbar_arrive(bfull + 16);
        if (it == 0) nbar_sync(1, 256);
        if (it < 3) conv_lda<0, LIN ? LIN : 16>(a0, pofs + pairs_of(it + 2));
        if (!LIN && it == 2) nbar_arrive(2, 256);
        TM(20 + (it >> 1) + wg * 16);
      }
      if (wg) {
        LOAD_SLICES();
        if (w == 0) {
          if (H1W) mbar_wait(bars + 8 * B_H1, 0);
          if (!(H1W && small_val(15))) { hint_wait(P.cnt + (N_H + 1) * 32, small_val(N_H + 1)); mbar_wait(bars + 8 * B_YE, 1); __syncwarp();
            if (elect()) { asm volatile("fence.proxy.async.global;" ::: "memory"); load_slices(0, 2, bars + 8 * B_A); load_slices(2, 4, bars + 8 * (B_A + 1)); } __syncwarp(); }
        }
        if (w == 1) hint_wait(P.cnt + (N_H + 2) * 32, small_val(N_H + 2));
        if (w != 1) nbar_arrive(2, 256);
        else {
        nbar_sync(2, 256);
        TM(12);
        if (elect()) { asm volatile("fence.proxy.async.global;" ::: "memory"); load_slices(4, 6, bars + 8 * (B_A + 2)); } }
        __syncwarp();
        TM(15);
      }
    }
    asm volatile("setmaxnreg.inc.sync.aligned.u32 240;");
    FRESH_IDS();
    const bool leader = tl == 0;
    const uint32_t reg = sb + M_PARK + wg * 8192;
    const uint32_t lma = (((lane >> 4) * 8 + (lane & 7)) * 128) + (((((lane >> 3) & 1) + 2 * w) ^ (lane & 7)) * 16);
    uint32_t a[144];
    float r0, r1, m0, m1;
    const uint32_t tf = small_val(N_F);
    if (T1) mbar_wait(bars + 8 * B_FULL, 0);
#pragma unroll 1
    for (int pass = 0;; pass++) {
      float sa[4] = {0.f, 0.f, 0.f, 0.f}, g0[4] = {0.f, 0.f, 0.f, 0.f}, g1[4] = {0.f, 0.f, 0.f, 0.f}, g2[4] = {0.f, 0.f, 0.f, 0.f}, g3[4] = {0.f, 0.f, 0.f, 0.f};
      auto group = [&](auto GR, auto K0, auto K1) {
        constexpr int gr = decltype(GR)::value, k0 = decltype(K0)::value, k1 = decltype(K1)::value;
        mbar_wait(bars + 8 * (B_A + gr), 0);
        if (gr == 0 || gr == 4) TM(gr ? 23 + wg * 16 : 58 + wg);
#pragma unroll
        for (int k = k0; k < k1; k++) ldsm4t(a[4 * k], a[4 * k + 1], a[4 * k + 2], a[4 * k + 3], reg + lma + (k >> 2) * 16384 + (k & 3) * 2048);
#pragma unroll
        for (int k = k0; k < k1; k++) {
          if (ST1) {
            mma1688(g0, a[4 * k], 0x3f803f80u, a[4 * k]); mma1688(g1, a[4 * k + 1], 0x3f803f80u, a[4 * k + 1]);
            mma1688(g2, a[4 * k + 2], 0x3f803f80u, a[4 * k + 2]); mma1688(g3, a[4 * k + 3], 0x3f803f80u, a[4 * k + 3]);
          } else { mma16816(sa, &a[4 * k], 0x3f803f80u, 0x3f803f80u);
          mma1688(g0, a[4 * k], a[4 * k + 1], a[4 * k]); mma1688(g1, a[4 * k], a[4 * k + 1], a[4 * k + 1]);
          mma1688(g2, a[4 * k + 2], a[4 * k + 3], a[4 * k + 2]); mma1688(g3, a[4 * k + 2], a[4 * k + 3], a[4 * k + 3]); } }
        asm volatile("" : "+f"(sa[0]), "+f"(g0[0]), "+f"(g1[0]), "+f"(g2[0]), "+f"(g3[0])::"memory");
      };
      group(IC<0>{}, IC<0>{}, IC<8>{}); group(IC<1>{}, IC<8>{}, IC<16>{}); group(IC<2>{}, IC<16>{}, IC<24>{}); if (G3S) { group(IC<3>{}, IC<24>{}, IC<28>{}); group(IC<B_A7 - B_A>{}, IC<28>{}, IC<32>{}); } else group(IC<3>{}, IC<24>{}, IC<32>{}); group(IC<4>{}, IC<32>{}, IC<36>{});
      if (ST1) {
        const int src = (lane & ~3) | (g >> 1);
        m0 = __shfl_sync(~0u, (g & 1) ? g0[3] + g2[3] : g0[2] + g2[2], src) * (1.f / D_); m1 = __shfl_sync(~0u, (g & 1) ? g1[3] + g3[3] : g1[2] + g3[2], src) * (1.f / D_);
        r0 = (g & 1) ? g0[1] + g2[1] : g0[0] + g2[0]; r1 = (g & 1) ? g1[1] + g3[1] : g1[0] + g3[0];
      } else {
      m0 = sa[0] * (1.f / D_); m1 = sa[2] * (1.f / D_);
      r0 = (g & 1) ? g0[1] + g2[1] : g0[0] + g2[0]; r1 = (g & 1) ? g1[3] + g3[3] : g1[2] + g3[2]; }
      uint32_t bad;
      asm volatile("{.reg .pred p, q; setp.eq.u32 q, %3, 128; setp.nan.or.f32 p, %1, %2, q; bar.red.or.pred q, 6, 256, p; selp.u32 %0, 1, 0, q;}"
                   : "=r"(bad) : "f"(T1 ? m0 : m0 + r0), "f"(T1 ? m1 : m1 + r1), "r"(tf) : "memory");
      if (!bad || pass) break;
      if (tid == 0) { grid_wait(P.cnt + N_F * 32, tf); PROXY_FENCE_SMEM(); mbar_expect(bars + 8 * B_RE, 9 * 16384);
#pragma unroll 1
        for (int s = 0; s < 9; s++) tma3d(sb + M_PARK + s * 16384, &P.tm_h2, 0, ((tf >> 7) & 1) * D_ + s * 64, 2 * m, bars + 8 * B_RE); }
      __syncwarp();
      mbar_wait(bars + 8 * B_RE, 0);
    }
    float d0[32], d1[32];
    uint32_t park = reg + tl * 16, ba = sb + M_BIAS + t4 * 8;
    float bv[4];
    {
      const uint32_t n0 = pack(m0, m0), n1 = pack(m1, m1);
      if (T1 == 2 && wg) nbar_sync(14, 256);
      center<0>(a, n0, n1);
      if (T1 == 2 && !wg) nbar_arrive(14, 256);
      if (!T1) mbar_wait(bars + 8 * B_FULL, 0);
      TM(24 + wg * 16); TC(0);
#pragma unroll
      for (int sg = 0; sg < 4; sg++) {
        mma_stage(d0, a, sg);
        mbar_wait_hot(bars + 8 * (B_FULL + ((sg + 1) & 3)), sg == 3);
        if (sg == 0) center<36>(a, n0, n1);
        if (sg == 1) center<72>(a, n0, n1);
        if (sg == 2) center<108>(a, n0, n1);
        if (sg == 3) { const int src = (lane & ~3) | (g >> 1);
          r0 = 0.5f * rsqrtf(fmaxf(fmaf(-m0, m0, __shfl_sync(~0u, r0, src) * (1.f / D_)), 0.f) + 1e-5f);
          r1 = 0.5f * rsqrtf(fmaxf(fmaf(-m1, m1, __shfl_sync(~0u, r1, src) * (1.f / D_)), 0.f) + 1e-5f);
          ld_bias(bv, ba); asm volatile("" : "+f"(r0), "+f"(r1)::"memory"); mbar_wait(bars + 8 * B_KV, 0); }
        WG_WAIT0();
        if (leader) mbar_arrive(bars + 8 * (B_EMPTY + sg));
      }
      pin(d0);
      TC(1);
    }
#pragma unroll 1
    for (int c = 0; c < 4; c++) {
      chunk1<false>(false, d1, d0, a, bars, 1, park, ba, leader, r0, r1, bv);
      TC(2 + 2 * c);
      chunk1<true>(c == 3, d0, d1, a, bars, 0, park + 16384, ba + 256, leader, r0, r1, bv);
      TC(3 + 2 * c);
      park += 32768; ba += 512;
    }
    TM(25 + wg * 16); TC(10);
    park -= 8 * 16384;
    uint32_t tag, io;
    auto send = [&](const char* outp) {
#pragma unroll
      for (int i = 0; i < 4; i++)
        asm volatile("st.relaxed.gpu.global.v4.u32 [%0], {%1,%2,%3,%4};" ::"l"(outp + i * 512), "r"((pack(d1[8 * i], d1[8 * i + 1]) & ~1u) | tag), "r"(pack(d1[8 * i + 2], d1[8 * i + 3])),
                     "r"(pack(d1[8 * i + 4], d1[8 * i + 5])), "r"(pack(d1[8 * i + 6], d1[8 * i + 7])) : "memory");
    };
    {
      const char* outp;
#pragma unroll
      for (int sg = 0; sg < 4; sg++) {
        mma_stage(d1, a, sg);
        mbar_wait_hot(bars + 8 * (sg < 3 ? B_FULL + sg + 1 : B_FULL + 8), sg < 3);
        if (sg == 0) gelu_last<0, 3, 18, 23>(d0, r0, r1, ba, a, park);
        if (sg == 1) gelu_last<3, 6, 23, 27>(d0, r0, r1, ba, a, park);
        if (sg == 2) gelu_last<6, 8, 27, 32>(d0, r0, r1, ba, a, park);
        if (sg == 3) {
#pragma unroll
          for (int n = 0; n < 16; n++) asm volatile("ld.shared.v2.f32 {%0,%1}, [%2];" : "=f"(d0[2 * n]), "=f"(d0[2 * n + 1]) : "r"(sb + M_B2 + t4 * 8 + (n >> 1) * 32) : "memory");
          tag = ((small_val(N_F) >> 7) & 1) ^ (tid >> 10); io = (b << DSH) | ((tid & 31) << 4) | ((tid >> 5) << 11);
          outp = (const char*)P.part + (((b & ~7) << DSH) | ((tid >> 5) << DSH) | (j << 11) | ((tid & 31) << 4));
          asm volatile("" : "+l"(outp), "+r"(tag), "+r"(io));
        }
        mbar_wait(bars + 8 * (sg < 3 ? B_KV : B_FULL + 9), 0);
        WG_WAIT0();
        if (leader && sg < 3) mbar_arrive(bars + 8 * (B_EMPTY + sg));
      }
      pin(d1);
      TC(11);
      send(outp);
      if (leader) mbar_arrive(bars + 8 * (B_EMPTY + 3));
    }
    uint32_t pi[16];
#pragma unroll
    for (int i = 0; i < 16; i++) asm volatile("" : "=r"(pi[i]));
    uint32_t dlo = (uint32_t)mkdesc(SB + M_PARK, 16384, 1024, 1), bb = bars + 64;
#pragma unroll 1
    for (int s = 1;; s++) {
      const uint32_t ph = ((s >> 1) ^ s ^ 1) & 1;
      const uint64_t buf16 = (mkdesc(0, 16384, 1024, 1) & 0xffffffff00000000ull) | dlo;
      const char* outp = nullptr;
      auto add_peer = [&](int i) { uint32_t u[4]; lds128(u[0], u[1], u[2], u[3], park + 6 * 16384 + i * 2048);
#pragma unroll
        for (int r = 0; r < 4; r++) { d0[8 * i + 2 * r] += blo(u[r]); d0[8 * i + 2 * r + 1] += bhi(u[r]); asm volatile("" : "+f"(d0[8 * i + 2 * r]), "+f"(d0[8 * i + 2 * r + 1])::"memory"); } };
      mma_half(d1, a, 0, buf16);
      if (s >= 3) { add_part<NB_, 16>(d0, pi); mbar_wait(bars + 8 * (B_HINT + s - 2), 0); ld_part(pi, (const char*)P.part + (io + ((s - 2) << SSH)));
        if (s == 8) { mbar_wait(bars + 8 * (B_PEER + wg), 0); add_peer(0); add_peer(1); } }
      else if (s == 2) { mbar_wait(bars + 8 * B_H, 0);
#pragma unroll
        for (int i = 0; i < 4; i++) ldsm4t(pi[4 * i], pi[4 * i + 1], pi[4 * i + 2], pi[4 * i + 3], reg + 8 * 16384 + lma + i * 2048);
      }
      mbar_wait(bb + 8 * (B_FULL + 2), ph); mbar_wait(bb + 8 * (B_FULL + 3), ph);
      WG_WAIT0();
      if (leader) { mbar_arrive(bb + 8 * B_EMPTY); mbar_arrive(bb + 8 * (B_EMPTY + 1)); }
      mma_half(d1, a, 1, buf16);
      if (s == 8) { add_peer(2); add_peer(3); }
      if (s >= 2) { if (s >= 3) poll_part(pi, P.part, io, s - 2, tag); add_part<0, NB_>(d0, pi); }
      if (s == 8) add_part<NB_, 16>(d0, pi);
      else { outp = (const char*)P.part + (io ^ ((s << SSH) | ((8 - s) << DSH))); asm volatile("" : "+l"(outp));
        const uint32_t nb = (bb ^ 64) + 8 * B_FULL; mbar_wait(nb, (s >> 1) & 1); mbar_wait(nb + 8, (s >> 1) & 1); }
      WG_WAIT0();
      pin(d1);
      TC(11 + s);
      if (s == 8) break;
      if (s < 7) send(outp);
      else {
        mbar_wait(bars + 8 * B_RDY, 0);
#pragma unroll
        for (int i = 0; i < 4; i++)
          asm volatile("st.async.weak.shared::cluster.mbarrier::complete_tx::bytes.v4.b32 [%0], {%1,%2,%3,%4}, [%5];" ::"r"((park ^ PEER) + 6 * 16384 + i * 2048),
                       "r"(pack(d1[8 * i], d1[8 * i + 1])), "r"(pack(d1[8 * i + 2], d1[8 * i + 3])), "r"(pack(d1[8 * i + 4], d1[8 * i + 5])), "r"(pack(d1[8 * i + 6], d1[8 * i + 7])),
                       "r"((bars ^ PEER) + 8 * (B_PEER + wg)) : "memory");
        TM(27 + wg * 16);
      }
      if (leader) { mbar_arrive(bb + 8 * (B_EMPTY + 2)); mbar_arrive(bb + 8 * (B_EMPTY + 3)); }
      bb ^= 64; dlo ^= ((SB + M_PARK) ^ (SB + M_RING)) >> 4;
    }
    TM(28 + wg * 16);
    const uint32_t ob = reg + 8 * 16384 + w * 2048;
    const int orow = lane & 15;
#pragma unroll
    for (int i = 0; i < 4; i++) {
      uint32_t o[4];
#pragma unroll
      for (int r = 0; r < 4; r++) o[r] = pack(d0[8 * i + 2 * r] + d1[8 * i + 2 * r], d0[8 * i + 2 * r + 1] + d1[8 * i + 2 * r + 1]);
      stsm4(ob + orow * 128 + (((2 * i + (lane >> 4)) ^ (orow & 7)) * 16), o[0], o[1], o[2], o[3]);
    }
    {
      __syncwarp();
      uint4* op = (uint4*)(P.out + (m * 128 + wg * 64 + w * 16 + (lane >> 3)) * D_ + j * 64) + (lane & 7);
#pragma unroll
      for (int i = 0; i < 4; i++) { uint4 v; const int row = 4 * i + (lane >> 3); lds128(v.x, v.y, v.z, v.w, ob + row * 128 + (((lane & 7) ^ (row & 7)) * 16)); __stcg(op + i * 4 * (D_ / 8), v); }
    }
    __syncwarp();
    TM(29 + wg * 16);
    TMFLUSH();
  }
}

typedef CUresult (*EncFn)(CUtensorMap*, CUtensorMapDataType, cuuint32_t, void*, const cuuint64_t*, const cuuint64_t*, const cuuint32_t*, const cuuint32_t*,
                          CUtensorMapInterleave, CUtensorMapSwizzle, CUtensorMapL2promotion, CUtensorMapFloatOOBfill);
void mk2d(EncFn enc, CUtensorMap* m, void* p, uint64_t inner, uint64_t outer, uint32_t bi, uint32_t bo, CUtensorMapSwizzle sw = CU_TENSOR_MAP_SWIZZLE_128B) {
  cuuint64_t d[2] = {inner, outer}, s[1] = {inner * 2}; cuuint32_t b[2] = {bi, bo}, e[2] = {1, 1};
  enc(m, CU_TENSOR_MAP_DATA_TYPE_BFLOAT16, 2, p, d, s, b, e, CU_TENSOR_MAP_INTERLEAVE_NONE, sw, CU_TENSOR_MAP_L2_PROMOTION_L2_128B, CU_TENSOR_MAP_FLOAT_OOB_FILL_NONE);
}
}

extern "C" void kernel_launch(void* const* d_in, const int* in_sizes, int n_in, void* d_out, int out_size) {
  void* f = nullptr; cudaDriverEntryPointQueryResult qr;
  cudaGetDriverEntryPoint("cuTensorMapEncodeTiled", &f, cudaEnableDefault, &qr);
  EncFn enc = (EncFn)f;
  void* hT; cudaGetSymbolAddress(&hT, g_hT);
  Params P;
  mk2d(enc, &P.tm_w1, d_in[7], F_, D_, 64, 144); mk2d(enc, &P.tm_w2, d_in[9], D_, F_, 64, 144);
  P.q = (const uint16_t*)d_in[0]; P.k = (const uint16_t*)d_in[1]; P.v = (const uint16_t*)d_in[2]; P.sk = (const uint16_t*)d_in[3]; P.ssk = (const uint16_t*)d_in[4];
  P.Dv = (const uint16_t*)d_in[5]; P.w1 = (const uint16_t*)d_in[7]; P.b1 = (const uint16_t*)d_in[8]; P.w2 = (const uint16_t*)d_in[9]; P.b2 = (const uint16_t*)d_in[10];
  P.out = (uint16_t*)d_out; P.hT = (uint16_t*)hT;
  cudaGetSymbolAddress((void**)&P.kvT, g_kvT); cudaGetSymbolAddress((void**)&P.xT, g_xT); cudaGetSymbolAddress((void**)&P.st1, g_st1);
  cudaGetSymbolAddress((void**)&P.part, g_part); cudaGetSymbolAddress((void**)&P.cnt, g_cnt); P.tm = nullptr;
  mk2d(enc, &P.tm_x, P.xT, S_, D_, 16, 64, CU_TENSOR_MAP_SWIZZLE_NONE);
  { cuuint64_t d[3] = {S_, D_ / 4, 4}, st[2] = {4 * S_ * 2, S_ * 2}; cuuint32_t bx[3] = {16, 16, 4}, e[3] = {1, 1, 1};
    enc(&P.tm_kv, CU_TENSOR_MAP_DATA_TYPE_BFLOAT16, 3, P.kvT, d, st, bx, e, CU_TENSOR_MAP_INTERLEAVE_NONE, CU_TENSOR_MAP_SWIZZLE_NONE, CU_TENSOR_MAP_L2_PROMOTION_NONE, CU_TENSOR_MAP_FLOAT_OOB_FILL_NONE); }
  { cuuint64_t d[3] = {64, 2 * D_, S_ / 64}, st[2] = {S_ * 2, 128}; cuuint32_t bx[3] = {64, 64, 2}, e[3] = {1, 1, 1};
    enc(&P.tm_h2, CU_TENSOR_MAP_DATA_TYPE_BFLOAT16, 3, P.hT, d, st, bx, e, CU_TENSOR_MAP_INTERLEAVE_NONE, CU_TENSOR_MAP_SWIZZLE_128B, CU_TENSOR_MAP_L2_PROMOTION_L2_128B, CU_TENSOR_MAP_FLOAT_OOB_FILL_NONE); }
  { cuuint64_t d[4] = {64, 64, S_ / 64, 18}, st[3] = {S_ * 2, 128, 64 * S_ * 2}; cuuint32_t bx[4] = {64, 64, 2, 2}, e[4] = {1, 1, 1, 1};
    enc(&P.tm_h4, CU_TENSOR_MAP_DATA_TYPE_BFLOAT16, 4, P.hT, d, st, bx, e, CU_TENSOR_MAP_INTERLEAVE_NONE, CU_TENSOR_MAP_SWIZZLE_128B, CU_TENSOR_MAP_L2_PROMOTION_L2_128B, CU_TENSOR_MAP_FLOAT_OOB_FILL_NONE); }
  cudaFuncSetAttribute(k_fused, cudaFuncAttributeMaxDynamicSharedMemorySize, M_SMEM);
  k_fused<<<128, 384, M_SMEM>>>(P);
}
```
